```python
import torch

def _softmax(x, axis=-1):
    return torch.softmax(x, dim=axis)
def _gelu(x):
    return torch.nn.functional.gelu(x, approximate="tanh")
def _silu(x):
    return torch.nn.functional.silu(x)
def _sigmoid(x):
    return torch.sigmoid(x)
def _layernorm(x, axis=-1, eps=1e-5):
    m = x.mean(dim=axis, keepdim=True)
    v = x.var(dim=axis, keepdim=True, unbiased=False)
    return (x - m) / torch.sqrt(v + eps)
def _scatter_add(tgt, idx, src, axis=0):
    return tgt.clone().index_add_(axis, idx, src)
def _segment_sum(src, seg, n):
    out = torch.zeros((n,) + src.shape[1:], dtype=src.dtype)
    return out.index_add_(0, seg, src)
def _pad(x, pw):
    flat = tuple(v for pair in reversed(pw) for v in pair)
    return torch.nn.functional.pad(x, flat)

kernel_name = 'standalone__mpnn_edge_mlp__graph'

def setup_inputs():

    _w = (lambda a: (lambda t: t.to(torch.bfloat16) if t.is_floating_point() else t)(torch.as_tensor(a)))
    N, deg, D, De = 10000, 16, 128, max(16, 1)
    E = N * deg
    return {
        "x": _w((lambda *s: torch.randn(*s, dtype=torch.bfloat16) * 0.05)(N, D)),
        "e_attr": _w((lambda *s: torch.randn(*s, dtype=torch.bfloat16) * 0.4)(E, De)),
        "src": _w((lambda lo, hi, *s: torch.randint(lo, hi, s))(0, N, E).to(torch.int64)),
        "dst": _w((lambda lo, hi, *s: torch.randint(lo, hi, s))(0, N, E).to(torch.int64)),
        "w_msg": _w((lambda *s: torch.randn(*s, dtype=torch.bfloat16) * 0.4)(2 * D + De, D)),
        "w_upd": _w((lambda *s: torch.randn(*s, dtype=torch.bfloat16) * 0.05)(2 * D, D)),
    }

def reference(x, e_attr, src, dst, w_msg, w_upd):
    N, D = x.shape
    m_in = torch.concatenate([x[src], x[dst], e_attr], axis=-1)
    msg = _silu(m_in @ w_msg)
    agg = _segment_sum(msg, dst, N)
    return _silu(torch.concatenate([x, agg], axis=-1) @ w_upd)
```

```cpp
#include <cuda_runtime.h>
#include <cuda_bf16.h>
#include <stdint.h>

namespace {

constexpr int D = 128;
constexpr int DE = 16;
constexpr int G = 132;
constexpr int NPC = 76;
constexpr int ROWS = 80;
constexpr int EPC = 1216;
constexpr int NT = 640;
constexpr int NMAX = G * NPC;
constexpr int EMAX = G * EPC;
constexpr int SEGCAP = 32;

constexpr int NTILE = 120;
constexpr int SM_XS = 0;
constexpr int SM_W = 20480;
constexpr int SM_AGG = SM_W + 65536;
constexpr int SM_EA = SM_AGG + 20480;
constexpr int SM_OUT = SM_EA;
constexpr int SM_LIST = SM_EA + 61440;
constexpr int SM_EL = SM_LIST + (NTILE + 4) * 64;
constexpr int SM_W3F = SM_EL + NTILE * 64;
constexpr int SM_MISC = SM_W3F + 4096;
constexpr int SM_STG = SM_AGG;
constexpr int SM_TOTAL = SM_MISC + 2816;
constexpr int SM_ALLOC = SM_TOTAL + 1024;
constexpr int MI_SEG = 0;
constexpr int MI_KEY = 544;
constexpr int MI_SLOW = 864;
constexpr int MI_PERM = 896;
constexpr int MI_SKEY = 1216;
constexpr int MI_NREC = 1536;
constexpr int MI_ID = 2176;

constexpr uint32_t W_EMPTY = 0xFFFFFFFFu;
constexpr uint32_t T_EMPTY = 0x7FFFFFFFu;
constexpr uint32_t T_OVF = 0x7FFFBFFFu;
constexpr int SPIN_LIMIT = 1 << 20;

__device__ __align__(256) __nv_bfloat16 g_P[(NMAX + G) * D];
__device__ __align__(256) uint32_t g_seg[G * G * SEGCAP];
__device__ __align__(256) uint32_t g_epoch[G * 8 + 64];
__device__ float g_aggf[4 * 1024 * 1024];
#define STAMP(i) do { } while (0)

__device__ __forceinline__ uint32_t smem_u32(const void* p) { return (uint32_t)__cvta_generic_to_shared(p); }
__device__ __forceinline__ void cp_async16(uint32_t dst, const void* src) {
    asm volatile("cp.async.cg.shared.global [%0], [%1], 16;" ::"r"(dst), "l"(src) : "memory");
}
__device__ __forceinline__ void cp_async16_z(uint32_t dst, const void* src, int bytes) {
    asm volatile("cp.async.cg.shared.global [%0], [%1], 16, %2;" ::"r"(dst), "l"(src), "r"(bytes) : "memory");
}
__device__ __forceinline__ void cp_commit() { asm volatile("cp.async.commit_group;" ::: "memory"); }
template <int N> __device__ __forceinline__ void cp_wait() { asm volatile("cp.async.wait_group %0;" ::"n"(N) : "memory"); }
__device__ __forceinline__ void fence_async() { asm volatile("fence.proxy.async.shared::cta;" ::: "memory"); }
__device__ __forceinline__ void bar_sync(int id, int n) { asm volatile("bar.sync %0, %1;" ::"r"(id), "r"(n) : "memory"); }
__device__ __forceinline__ void bar_arrive(int id, int n) { asm volatile("bar.arrive %0, %1;" ::"r"(id), "r"(n) : "memory"); }
__device__ __forceinline__ uint32_t lds32(uint32_t a) { uint32_t v; asm volatile("ld.shared.u32 %0, [%1];" : "=r"(v) : "r"(a) : "memory"); return v; }
__device__ __forceinline__ uint2 lds64(uint32_t a) { uint2 v; asm volatile("ld.shared.v2.u32 {%0,%1}, [%2];" : "=r"(v.x), "=r"(v.y) : "r"(a) : "memory"); return v; }
__device__ __forceinline__ uint4 lds128(uint32_t a) { uint4 v; asm volatile("ld.shared.v4.u32 {%0,%1,%2,%3}, [%4];" : "=r"(v.x), "=r"(v.y), "=r"(v.z), "=r"(v.w) : "r"(a) : "memory"); return v; }
__device__ __forceinline__ void sts32(uint32_t a, uint32_t v) { asm volatile("st.shared.u32 [%0], %1;" ::"r"(a), "r"(v) : "memory"); }
__device__ __forceinline__ void sts128(uint32_t a, uint4 v) { asm volatile("st.shared.v4.u32 [%0], {%1,%2,%3,%4};" ::"r"(a), "r"(v.x), "r"(v.y), "r"(v.z), "r"(v.w) : "memory"); }
__device__ __forceinline__ uint32_t atoms_add(uint32_t a, int d) { uint32_t v; asm volatile("atom.shared.add.u32 %0, [%1], %2;" : "=r"(v) : "r"(a), "r"(d) : "memory"); return v; }
__device__ __forceinline__ uint4 ldg128(const void* p) { uint4 v; asm volatile("ld.global.v4.u32 {%0,%1,%2,%3}, [%4];" : "=r"(v.x), "=r"(v.y), "=r"(v.z), "=r"(v.w) : "l"(p) : "memory"); return v; }
__device__ __forceinline__ uint2 ldg64(const void* p) { uint2 v; asm volatile("ld.global.v2.u32 {%0,%1}, [%2];" : "=r"(v.x), "=r"(v.y) : "l"(p) : "memory"); return v; }
__device__ __forceinline__ void sts64(uint32_t a, uint32_t x, uint32_t y) { asm volatile("st.shared.v2.u32 [%0], {%1,%2};" ::"r"(a), "r"(x), "r"(y) : "memory"); }
__device__ __forceinline__ uint32_t ldg32(const void* p) { uint32_t v; asm volatile("ld.global.u32 %0, [%1];" : "=r"(v) : "l"(p) : "memory"); return v; }
__device__ __forceinline__ void stg128(void* p, uint4 v) { asm volatile("st.global.v4.u32 [%0], {%1,%2,%3,%4};" ::"l"(p), "r"(v.x), "r"(v.y), "r"(v.z), "r"(v.w) : "memory"); }
__device__ __forceinline__ uint32_t pack_bf16(float lo, float hi) {
    uint32_t r; asm("cvt.rn.bf16x2.f32 %0, %1, %2;" : "=r"(r) : "f"(hi), "f"(lo)); return r;
}
__device__ __forceinline__ float tanh_fast(float x) { float r; asm("tanh.approx.f32 %0, %1;" : "=f"(r) : "f"(x)); return r; }
__device__ __forceinline__ float silu_half(float h) { return fmaf(h, tanh_fast(h), h); }
__device__ __forceinline__ uint32_t movm(uint32_t a) { uint32_t d; asm volatile("movmatrix.sync.aligned.m8n8.trans.b16 %0, %1;" : "=r"(d) : "r"(a)); return d; }
__device__ __forceinline__ uint32_t shl_clamp(uint32_t v, uint32_t s) { uint32_t d; asm("shl.b32 %0, %1, %2;" : "=r"(d) : "r"(v), "r"(s)); return d; }
__device__ __forceinline__ void mma16(float (&d)[4], uint32_t a0, uint32_t a1, uint32_t a2, uint32_t a3, uint32_t b0, uint32_t b1) {
    asm("mma.sync.aligned.m16n8k16.row.col.f32.bf16.bf16.f32 {%0,%1,%2,%3}, {%4,%5,%6,%7}, {%8,%9}, {%0,%1,%2,%3};"
        : "+f"(d[0]), "+f"(d[1]), "+f"(d[2]), "+f"(d[3]) : "r"(a0), "r"(a1), "r"(a2), "r"(a3), "r"(b0), "r"(b1));
}
__device__ __forceinline__ void mma16_c(float (&d)[4], uint32_t a0, uint32_t a1, uint32_t a2, uint32_t a3, uint32_t b0, uint32_t b1, const float (&c)[4]) {
    asm("mma.sync.aligned.m16n8k16.row.col.f32.bf16.bf16.f32 {%0,%1,%2,%3}, {%4,%5,%6,%7}, {%8,%9}, {%10,%11,%12,%13};"
        : "=f"(d[0]), "=f"(d[1]), "=f"(d[2]), "=f"(d[3]) : "r"(a0), "r"(a1), "r"(a2), "r"(a3), "r"(b0), "r"(b1),
          "f"(c[0]), "f"(c[1]), "f"(c[2]), "f"(c[3]));
}
__device__ __forceinline__ void stsm_x4_trans(uint32_t addr, uint32_t r0, uint32_t r1, uint32_t r2, uint32_t r3) {
    asm volatile("stmatrix.sync.aligned.m8n8.x4.trans.shared.b16 [%0], {%1,%2,%3,%4};" ::"r"(addr), "r"(r0), "r"(r1), "r"(r2), "r"(r3) : "memory");
}

__device__ __forceinline__ uint64_t make_desc(uint32_t addr) {
    return (uint64_t)((addr & 0x3FFFF) >> 4) | ((uint64_t)64 << 16) | ((uint64_t)64 << 32) | ((uint64_t)1 << 62);
}
__device__ __forceinline__ void wg_fence() { asm volatile("wgmma.fence.sync.aligned;" ::: "memory"); }
__device__ __forceinline__ void wg_commit() { asm volatile("wgmma.commit_group.sync.aligned;" ::: "memory"); }
template <int N> __device__ __forceinline__ void wg_wait() { asm volatile("wgmma.wait_group.sync.aligned %0;" ::"n"(N) : "memory"); }
__device__ __forceinline__ void wgmma_n80(float (&d)[40], uint64_t da, uint64_t db, int scale_d) {
    asm volatile(
        "{\n.reg .pred p;\nsetp.ne.b32 p, %42, 0;\n"
        "wgmma.mma_async.sync.aligned.m64n80k16.f32.bf16.bf16 "
        "{%0,%1,%2,%3,%4,%5,%6,%7,%8,%9,%10,%11,%12,%13,%14,%15,%16,%17,%18,%19,"
        "%20,%21,%22,%23,%24,%25,%26,%27,%28,%29,%30,%31,%32,%33,%34,%35,%36,%37,%38,%39}, "
        "%40, %41, p, 1, 1, 1, 0;\n}\n"
        : "+f"(d[0]), "+f"(d[1]), "+f"(d[2]), "+f"(d[3]), "+f"(d[4]), "+f"(d[5]), "+f"(d[6]), "+f"(d[7]), "+f"(d[8]), "+f"(d[9]),
          "+f"(d[10]), "+f"(d[11]), "+f"(d[12]), "+f"(d[13]), "+f"(d[14]), "+f"(d[15]), "+f"(d[16]), "+f"(d[17]), "+f"(d[18]), "+f"(d[19]),
          "+f"(d[20]), "+f"(d[21]), "+f"(d[22]), "+f"(d[23]), "+f"(d[24]), "+f"(d[25]), "+f"(d[26]), "+f"(d[27]), "+f"(d[28]), "+f"(d[29]),
          "+f"(d[30]), "+f"(d[31]), "+f"(d[32]), "+f"(d[33]), "+f"(d[34]), "+f"(d[35]), "+f"(d[36]), "+f"(d[37]), "+f"(d[38]), "+f"(d[39])
        : "l"(da), "l"(db), "r"(scale_d));
}

__device__ __forceinline__ uint4 ldg128_rlx(const void* p) { uint4 v; asm volatile("ld.relaxed.gpu.global.v4.u32 {%0,%1,%2,%3}, [%4];" : "=r"(v.x), "=r"(v.y), "=r"(v.z), "=r"(v.w) : "l"(p) : "memory"); return v; }
__device__ __forceinline__ void stg128_rlx(void* p, uint4 v) { asm volatile("st.relaxed.gpu.global.v4.u32 [%0], {%1,%2,%3,%4};" ::"l"(p), "r"(v.x), "r"(v.y), "r"(v.z), "r"(v.w) : "memory"); }

__device__ __forceinline__ void hint_arrive(uint32_t* p) { asm volatile("red.relaxed.gpu.global.add.u32 [%0], 1;" ::"l"(p) : "memory"); }
__device__ __forceinline__ void hint_wait(const uint32_t* p, uint32_t target) {
    for (int it = 0; it < SPIN_LIMIT; it++) {
        uint32_t v;
        asm volatile("ld.relaxed.gpu.global.u32 %0, [%1];" : "=r"(v) : "l"(p) : "memory");
        if ((int)(v - target) >= 0) break;
    }
}

__host__ __device__ constexpr int boundary(int k) { return 24 + 21 * k; }
__device__ __forceinline__ uint32_t ea_chunk(uint32_t pos) { return ((pos & ~15u) << 1) | ((pos & 1u) << 4) | (pos & 14u); }
__device__ __forceinline__ uint32_t tile_addr(uint32_t base, int row, int c) {
    return base + (c >> 3) * 10240 + row * 128 + (((c & 7) ^ (row & 7)) << 4);
}

struct Tile { uint4 p0, p1; };
struct Consts { uint4 w3[2]; uint4 id; uint32_t par; const unsigned char* pb; };

__device__ __forceinline__ void fetch(Tile& st, uint32_t la, const Consts& k) {
    uint2 e = lds64(la);
    st.p0 = ldg128_rlx(k.pb + (size_t)e.x * 256);
    st.p1 = ldg128_rlx(k.pb + (size_t)e.y * 256);
}
__device__ __forceinline__ bool stale(const Tile& a, const Tile& b, const Consts& k) {
    uint32_t t, u;
    asm("lop3.b32 %0, %1, %2, %3, 0x7E;" : "=r"(t) : "r"(a.p0.x), "r"(a.p1.x), "r"(k.par));
    asm("lop3.b32 %0, %1, %2, %3, 0x7E;" : "=r"(u) : "r"(b.p0.x), "r"(b.p1.x), "r"(k.par));
    asm("lop3.b32 %0, %1, %2, 1, 0xA8;" : "=r"(t) : "r"(t), "r"(u));
    return __any_sync(0xffffffffu, t != 0);
}
__device__ __forceinline__ void validate(Tile& a, Tile& b, uint32_t la, const Consts& k) {
    if (__builtin_expect(stale(a, b, k), 0)) {
        for (int it = 0; it < SPIN_LIMIT; it++) {
            fetch(a, la, k);
            fetch(b, la + 64, k);
            if (!stale(a, b, k)) break;
        }
    }
}
__device__ __forceinline__ void tile_mma(float (&acc)[2][4], const Tile& st, uint32_t ea, const float (&qi)[2][4], const Consts& k) {
    const uint2 ea0 = lds64(ea), ea1 = lds64(ea + 256);
    float c[2][2][4];
#pragma unroll
    for (int u = 0; u < 2; u++) {
        mma16_c(c[u][0], k.id.x, k.id.y, k.id.z, k.id.w, u ? st.p0.z : st.p0.x, u ? st.p0.w : st.p0.y, qi[u]);
        mma16_c(c[u][1], k.id.x, k.id.y, k.id.z, k.id.w, u ? st.p1.z : st.p1.x, u ? st.p1.w : st.p1.y, qi[u]);
    }
#pragma unroll
    for (int u = 0; u < 2; u++) {
        mma16(c[u][0], k.w3[u].x, k.w3[u].y, k.w3[u].z, k.w3[u].w, ea0.x, ea0.y);
        mma16(c[u][1], k.w3[u].x, k.w3[u].y, k.w3[u].z, k.w3[u].w, ea1.x, ea1.y);
    }
#pragma unroll
    for (int u = 0; u < 2; u++)
#pragma unroll
        for (int n = 0; n < 2; n++)
#pragma unroll
            for (int i = 0; i < 4; i++) acc[u][i] += silu_half(c[u][n][i]);
}
__device__ __forceinline__ void load_q(float (&qi)[2][4], uint32_t sb, int ra, int rb, int f, int g) {
    const uint4 a = lds128(tile_addr(sb + SM_AGG, ra, 4 * f + (g >> 1))), b = lds128(tile_addr(sb + SM_AGG, rb, 4 * f + (g >> 1)));
    const uint32_t sel = (g & 1) ? 0x3244u : 0x1044u;
    qi[0][0] = 0.5f * __uint_as_float(__byte_perm(a.x, 0, sel)); qi[0][1] = 0.5f * __uint_as_float(__byte_perm(b.x, 0, sel));
    qi[0][2] = 0.5f * __uint_as_float(__byte_perm(a.y, 0, sel)); qi[0][3] = 0.5f * __uint_as_float(__byte_perm(b.y, 0, sel));
    qi[1][0] = 0.5f * __uint_as_float(__byte_perm(a.z, 0, sel)); qi[1][1] = 0.5f * __uint_as_float(__byte_perm(b.z, 0, sel));
    qi[1][2] = 0.5f * __uint_as_float(__byte_perm(a.w, 0, sel)); qi[1][3] = 0.5f * __uint_as_float(__byte_perm(b.w, 0, sel));
}
__device__ __forceinline__ void flush_agg(uint32_t addr, const float (&acc)[2][4]) {
    uint4 v;
    v.x = movm(pack_bf16(acc[0][0], acc[0][1]));
    v.y = movm(pack_bf16(acc[0][2], acc[0][3]));
    v.z = movm(pack_bf16(acc[1][0], acc[1][1]));
    v.w = movm(pack_bf16(acc[1][2], acc[1][3]));
    sts128(addr, v);
}

__device__ __noinline__ void slow_path(uint32_t sb, const __nv_bfloat16* e_attr, const int* src, const int* dst, int E, Consts k) {
    const int tid = threadIdx.x, lane = tid & 31, wg = tid >> 7, f = (tid >> 5) & 3, g = lane >> 2, q = lane & 3, cta = blockIdx.x;
    const uint32_t s_deg = sb + SM_MISC + MI_KEY;
    float acc[2][2][4];
    for (int i = 0; i < 16; i++) (&acc[0][0][0])[i] = 0.f;
    int scan = 0, state = 0, row = 0;
    bool more = true;
    while (more) {
        more = false;
        __syncthreads();
        if (tid < ROWS) sts32(s_deg + tid * 4, 0);
        for (int i = tid; i < 3840; i += NT) sts128(sb + SM_EA + i * 16, make_uint4(0, 0, 0, 0));
        for (int i = tid; i < (NTILE + 4) * 16; i += NT) sts32(sb + SM_LIST + i * 4, NMAX + cta);
        __syncthreads();
        while (true) {
            const int e = scan + tid;
            if (state == 0) {
                state = 2;
                if (e < E) {
                    int dn = dst[e];
                    if (dn / NPC == cta) { state = 1; row = dn - cta * NPC; }
                }
            }
            if (state == 1) {
                uint32_t rank = atoms_add(s_deg + row * 4, 1);
                if (rank < 24) {
                    uint32_t pos = ((row >> 3) * 12 + (rank >> 1)) * 16 + (row & 7) * 2 + (rank & 1);
                    sts32(sb + SM_LIST + pos * 4, (uint32_t)src[e]);
                    sts128(sb + SM_EA + ea_chunk(pos) * 16, ldg128(e_attr + (size_t)e * DE));
                    sts128(sb + SM_EA + ea_chunk(pos) * 16 + 16, ldg128(e_attr + (size_t)e * DE + 8));
                    state = 2;
                }
            }
            if (__syncthreads_or(state == 1)) { more = true; break; }
            scan += NT;
            state = 0;
            if (scan >= E) break;
        }
#pragma unroll
        for (int b = 0; b < 2; b++) {
            const int grp = 2 * wg + b;
            const int mx = min((int)__reduce_max_sync(0xffffffffu, lds32(s_deg + (grp * 8 + g) * 4)), 24);
            float qi[2][4];
            load_q(qi, sb, grp * 8 + 2 * q, grp * 8 + 2 * q + 1, f, g);
            for (int t = 0; t * 2 < mx; t++) {
                const int tile = grp * 12 + t;
                Tile st, s2;
                const uint32_t la = sb + SM_LIST + tile * 64 + g * 8;
                fetch(st, la, k);
                fetch(s2, la + 64, k);
                validate(st, s2, la, k);
                tile_mma(acc[b], st, sb + SM_EA + tile * 512 + g * 32 + q * 8, qi, k);
            }
        }
    }
    __syncwarp();
    flush_agg(tile_addr(sb + SM_AGG, wg * 16 + g, 4 * f + q), acc[0]);
    flush_agg(tile_addr(sb + SM_AGG, wg * 16 + 8 + g, 4 * f + q), acc[1]);
}

__global__ void __launch_bounds__(NT, 1)
mpnn_kernel(const __nv_bfloat16* __restrict__ x, const __nv_bfloat16* __restrict__ e_attr,
            const int* __restrict__ src, const int* __restrict__ dst,
            const __nv_bfloat16* __restrict__ w_msg, const __nv_bfloat16* __restrict__ w_upd,
            __nv_bfloat16* __restrict__ out, __nv_bfloat16* __restrict__ gP, uint32_t* __restrict__ gseg,
            uint32_t* __restrict__ gepoch, int N, int E) {
    extern __shared__ unsigned char smem_raw[];
    const uint32_t sb = (smem_u32(smem_raw) + 1023u) & ~1023u;
    const int tid = threadIdx.x, warp = tid >> 5, lane = tid & 31;
    const int wg = warp >> 2, f = warp & 3, g = lane >> 2, q = lane & 3;
    const int cta = blockIdx.x;
    const uint32_t sm = sb + SM_MISC;
    const int nloc = N - cta * NPC;
    if (tid == 0) STAMP(0);

    uint2 d2 = make_uint2(~0u, 0), s2;
    {
        const int e0 = ((tid >> 4) * G + cta) * 32 + (tid & 15) * 2;
        if (tid < EPC / 2 && e0 < E) {
            d2 = ldg64(dst + e0);
            s2 = ldg64(src + e0);
        }
    }
    const uint32_t tag = ldg32(gepoch + cta * 8) + 1;
    sts128(sb + SM_STG + tid * 16, make_uint4(W_EMPTY, W_EMPTY, W_EMPTY, W_EMPTY));
    if (tid < 416) sts128(sb + SM_STG + 10240 + tid * 16, make_uint4(W_EMPTY, W_EMPTY, W_EMPTY, W_EMPTY));
    else if (tid < 633) sts32(sm + (tid - 416) * 4, (tid >= 552 && tid < 632) ? 127 - (tid - 552) : 0);
    __syncthreads();
    if (tid == 0) STAMP(23);
    uint32_t w3raw[16];
    if (wg < 4) {
        const int t = tid & 255, r0 = t >> 4, c = t & 15;
        const uint32_t sw = r0 * 128 + (((c & 7) ^ (r0 & 7)) << 4);
        const uint32_t d = sb + SM_W + (wg >> 1) * 32768 + (c >> 3) * 16384 + sw;
        const __nv_bfloat16* wp = w_msg + (wg >> 1) * D * D + t * 8;
#pragma unroll
        for (int i = 0; i < 8; i++) cp_async16(d + i * 2048, wp + i * 2048);
        const int p0 = (wg >> 1) * 3;
        const __nv_bfloat16* xp = x + (size_t)(cta * NPC + r0 + p0 * 16) * D + c * 8;
#pragma unroll
        for (int p = 0; p < 3; p++) {
            const bool ok = r0 + 16 * (p0 + p) < nloc;
            if (p0 + p < 5) cp_async16_z(sb + SM_XS + (c >> 3) * 10240 + sw + (p0 + p) * 2048, ok ? xp + 16 * p * D : x, ok ? 16 : 0);
        }
        cp_commit();
    } else {
        if (tid >= 628) {
            const int ln = cta * 4 + (tid - 628);
            const void* wp = tid < 632 ? static_cast<const void*>(reinterpret_cast<const unsigned char*>(w_upd) + min(ln, 511) * 128)
                                       : static_cast<const void*>(gepoch + G * 8);
            asm volatile("prefetch.global.L2 [%0];" ::"l"(wp));
        }
        const unsigned short* w3p = reinterpret_cast<const unsigned short*>(w_msg + 2 * D * D) + 4 * q * D + 32 * f + (g >> 1) * 8 + (g & 1);
#pragma unroll
        for (int i = 0; i < 16; i++) {
            const int u = i >> 3, r = (i >> 1) & 3, o = 4 * u + 2 * (r & 1) + (2 * (r >> 1) + (i & 1)) * D;
            unsigned short v;
            asm volatile("ld.global.nc.u16 %0, [%1];" : "=h"(v) : "l"(w3p + o));
            w3raw[i] = v;
        }
    }
    {
        const uint32_t pr = NMAX + cta;
        if (tid < 496) sts128(sb + SM_LIST + tid * 16, make_uint4(pr, pr, pr, pr));
        if (tid >= 160) sts128(sb + SM_EL + (tid - 160) * 16, make_uint4(1, 1, 1, 1));
        else if (tid < 32) {
            uint32_t idf = shl_clamp(0x3F00u, (uint32_t)((g - 2 * q) << 4));
            sts128(sm + MI_ID + lane * 16, make_uint4(idf, 0, 0, idf));
        }
    }
    if (d2.x != ~0u) {
        const uint32_t dc0 = d2.x / NPC, dc1 = d2.y / NPC;
        const uint32_t r0 = atoms_add(sm + MI_SEG + dc0 * 4, 1), r1 = atoms_add(sm + MI_SEG + dc1 * 4, 1);
        const uint32_t w0 = s2.x | (((tid << 8) + d2.x - dc0 * NPC) << 14), w1 = s2.y | (((tid << 8) + 128 + d2.y - dc1 * NPC) << 14);
        if (r0 < SEGCAP) sts32(sb + SM_STG + dc0 * 128 + (r0 & 7) * 16 + (r0 >> 3) * 4, w0);
        if (r1 < SEGCAP) sts32(sb + SM_STG + dc1 * 128 + (r1 & 7) * 16 + (r1 >> 3) * 4, w1);
    }
    if (tid == 0) STAMP(24);
    __syncthreads();
    const uint32_t parw = tag << 31;
    {
        uint4 v[2];
        uint32_t cn[2];
#pragma unroll
        for (int i = 0; i < 2; i++) {
            v[i] = lds128(sb + SM_STG + tid * 16 + i * 10240);
            cn[i] = lds32(sm + MI_SEG + ((tid >> 3) + i * 80) * 4);
        }
#pragma unroll
        for (int i = 0; i < 2; i++) {
            uint32_t tl = T_EMPTY;
            if (cn[i] > 24) {
                const uint32_t w = v[i].w;
                if (w != W_EMPTY) tl = (((w >> 21) * ROWS + ((w >> 14) & 127u)) << 14) | (w & 16383u);
                if (cn[i] > SEGCAP) tl = T_OVF;
            }
            v[i].w = tl | parw;
            if (i == 0 || tid < 416) stg128_rlx(gseg + (size_t)cta * (G * SEGCAP) + tid * 4 + i * 2560, v[i]);
        }
    }
    if (wg < 4) {
        bar_arrive(2, 640);
        cp_wait<0>();
        fence_async();
        bar_sync(1, 640);
        if (tid == 0) STAMP(1);
        if (tid == 511) {
            int eb = cta * EPC, ne = min(EPC, E - eb);
            if (ne > 0) asm volatile("cp.async.bulk.prefetch.L2.global [%0], %1;" ::"l"(e_attr + (size_t)eb * DE), "r"(ne * 32) : "memory");
        }
        float acc[40];
        const uint32_t box = sb + SM_W + wg * 16384;
        {
            const uint64_t da = make_desc(box), db = make_desc(sb + SM_XS);
            wg_fence();
#pragma unroll
            for (int ks = 0; ks < 8; ks++) wgmma_n80(acc, da + ks * 128, db + (ks >> 2) * 640 + (ks & 3) * 2, ks);
            wg_commit();
        }
        const int t2 = tid & 127, r8 = t2 >> 3, c8 = t2 & 7;
        const uint32_t sw8 = r8 * 128 + ((c8 ^ (r8 & 7)) << 4);
        const uint32_t so = (wg < 2 ? box : sb + SM_AGG + (wg - 2) * 10240) +
                            (((lane >> 4) & 1) * 8 + (lane & 7)) * 128 + (((f * 2 + ((lane >> 3) & 1)) ^ (lane & 7)) << 4);
        wg_wait<0>();
        if (tid == 0) STAMP(2);
        if (wg < 2) bar_sync(7 + wg, 128);
#pragma unroll
        for (int j = 0; j < 5; j++)
            stsm_x4_trans(so + j * 2048,
                          pack_bf16(acc[8 * j], acc[8 * j + 1]), pack_bf16(acc[8 * j + 2], acc[8 * j + 3]),
                          pack_bf16(acc[8 * j + 4], acc[8 * j + 5]), pack_bf16(acc[8 * j + 6], acc[8 * j + 7]));
        if (wg < 2) {
            bar_sync(7 + wg, 128);
            __nv_bfloat16* pp = gP + (size_t)(cta * NPC + r8) * D + wg * 64 + c8 * 8;
#pragma unroll
            for (int p = 0; p < 5; p++) {
                uint4 v = lds128(box + sw8 + p * 2048);
                v.x = (v.x & ~1u) | (tag & 1u);
                if (p < 4 || r8 < NPC - 64) stg128_rlx(pp + 16 * p * D, v);
            }
            if (tid == 0) STAMP(3);
        }
    } else {
        bar_arrive(1, 640);
        bar_sync(2, 640);
        if (tid == 512) {
            STAMP(4);
            hint_arrive(gepoch + G * 8);
            hint_wait(gepoch + G * 8, tag * G);
            STAMP(7);
        }
        uint32_t w[8];
#pragma unroll
        for (int i = 0; i < 8; i++)
            asm("mul.bf16x2 %0, %1, %2;" : "=r"(w[i]) : "r"(w3raw[2 * i] | (w3raw[2 * i + 1] << 16)), "r"(0x3F003F00u));
        sts128(sb + SM_W3F + f * 1024 + lane * 16, make_uint4(w[0], w[1], w[2], w[3]));
        sts128(sb + SM_W3F + f * 1024 + 512 + lane * 16, make_uint4(w[4], w[5], w[6], w[7]));
        if (tid >= 624)
            stg128_rlx(gP + (size_t)(NMAX + cta) * D + (tid - 624) * 8, make_uint4(0xFF00FF00u | (tag & 1u), 0xFF00FF00u, 0xFF00FF00u, 0xFF00FF00u));
    }
    __syncthreads();
    if (tid == 0) STAMP(22);
    {
        const uint32_t* bp = gseg + ((size_t)(tid >> 3) * G + cta) * SEGCAP + (tid & 7) * 4;
        uint4 v0, v1 = make_uint4(W_EMPTY, W_EMPTY, W_EMPTY, T_EMPTY | parw);
        v0 = ldg128_rlx(bp);
        if (tid < 416) v1 = ldg128_rlx(bp + (size_t)80 * G * SEGCAP);
        if (wg < 4) {
            const int t2 = tid & 127, r8 = t2 >> 3, c8 = t2 & 7;
            const __nv_bfloat16* wp = w_upd + ((wg >> 1) * D + r8) * D + (wg & 1) * 64 + c8 * 8;
            const uint32_t d = sb + SM_W + wg * 16384 + r8 * 128 + ((c8 ^ (r8 & 7)) << 4);
#pragma unroll
            for (int i = 0; i < 8; i++) cp_async16(d + i * 2048, wp + i * 16 * D);
        }
        for (int it = 0; it < SPIN_LIMIT; it++) {
            if (!__any_sync(0xffffffffu, (int)((v0.w ^ parw) | (v1.w ^ parw)) < 0)) break;
            v0 = ldg128_rlx(bp);
            if (tid < 416) v1 = ldg128_rlx(bp + (size_t)80 * G * SEGCAP);
        }
        if (tid == 0) STAMP(8);
        uint32_t en[8] = {v0.x, v1.x, v0.y, v1.y, v0.z, v1.z, W_EMPTY, W_EMPTY}, rk[8];
        const bool deep = __any_sync(0xffffffffu, (v0.z & v1.z) != W_EMPTY);
#pragma unroll
        for (int i = 0; i < 4; i++)
            if (en[i] != W_EMPTY) rk[i] = atoms_add(sm + MI_KEY + ((en[i] >> 12) & 508u), 128);
        if (deep) {
#pragma unroll
            for (int r = 0; r < 2; r++) {
                const uint32_t tl = (r ? v1.w : v0.w) & T_EMPTY, er = tl >> 14, el = ((er >> 4) * 52429u) >> 18;
                if (tl == T_OVF) sts32(sm + MI_SLOW, 1);
                if (tl < T_OVF) en[6 + r] = (el << 21) | ((er - el * ROWS) << 14) | (tl & 16383u);
            }
#pragma unroll
            for (int i = 4; i < 8; i++)
                if (en[i] != W_EMPTY) rk[i] = atoms_add(sm + MI_KEY + ((en[i] >> 12) & 508u), 128);
        }
        __syncthreads();
        if (tid == 0) STAMP(9);
        {
            const uint32_t key = lds32(sm + MI_KEY + (tid >> 3) * 4);
            int sp = 0;
#pragma unroll
            for (int i = 0; i < 5; i++) {
                const uint2 o = lds64(sm + MI_KEY + (tid & 7) * 40 + i * 8);
                sp += (o.x > key) + (o.y > key);
            }
            sp += __shfl_xor_sync(0xffffffffu, sp, 1);
            sp += __shfl_xor_sync(0xffffffffu, sp, 2);
            sp += __shfl_xor_sync(0xffffffffu, sp, 4);
            if ((tid & 7) == 0) {
                const int grp = sp >> 3;
                const bool down = grp < 5;
                sts32(sm + MI_PERM + sp * 4, tid >> 3);
                sts32(sm + MI_SKEY + sp * 4, key);
                sts64(sm + MI_NREC + tid, boundary(down ? grp : 9 - grp) * 16 + (sp & 7) * 2 + (down ? -14 : 0), down ? ~0u : 0u);
            }
        }
        __syncthreads();
        if (tid == 0) STAMP(25);
        auto place = [&](int i) {
            if (en[i] != W_EMPTY) {
                const uint2 nr = lds64(sm + MI_NREC + ((en[i] >> 11) & 1016u));
                const uint32_t off = ((rk[i] >> 4) & ~15u) | ((rk[i] >> 7) & 1u);
                const uint32_t ps = min(nr.x + (off ^ nr.y), (uint32_t)(NTILE * 16 - 1));
                const uint32_t el = en[i] >> 21;
                sts32(sb + SM_LIST + ps * 4, en[i] & 16383u);
                sts32(sb + SM_EL + ps * 4, (el + (el >> 5) * (G * 32 - 32) + ((tid >> 3) + (i & 1) * 80) * 32) * 32);
            }
        };
#pragma unroll
        for (int i = 0; i < 4; i++) place(i);
        if (deep) {
#pragma unroll
            for (int i = 4; i < 8; i++) place(i);
        }
    }
    if (tid == 0) STAMP(11);
    __syncthreads();
    if (tid == 0) STAMP(13);

    Consts k;
    k.par = tag;
    k.pb = reinterpret_cast<const unsigned char*>(gP) + f * 64 + q * 16;
    int nt;
    bool slow;
    {
        const int l = min(lane, 9);
        nt = (int)((lds32(sm + MI_SKEY + l * 32) >> 7) + 1) >> 1;
        const int other = __shfl_sync(0xffffffffu, nt, (10 - l) % 10);
        const int lim = l == 0 ? 48 : l == 5 ? 24 : 21;
        slow = __any_sync(0xffffffffu, nt + other > lim) || lds32(sm + MI_SLOW) != 0;
    }
    if (slow) {
        k.w3[0] = lds128(sb + SM_W3F + f * 1024 + lane * 16);
        k.w3[1] = lds128(sb + SM_W3F + f * 1024 + 512 + lane * 16);
        k.id = lds128(sm + MI_ID + lane * 16);
        cp_commit();
        cp_wait<0>();
        slow_path(sb, e_attr, src, dst, E, k);
    } else {
        const int tsw = (int)__reduce_max_sync(0xffffffffu, (uint32_t)boundary(wg));
        int t = tsw - (int)__reduce_max_sync(0xffffffffu, lane == wg ? nt : 0);
        const int tend = tsw + (int)__reduce_max_sync(0xffffffffu, lane == 9 - wg ? nt : 0);
        const unsigned char* eb = reinterpret_cast<const unsigned char*>(e_attr) + (lane & 1) * 16;
        const uint32_t gd = sb + SM_EA + f * 512 + (ea_chunk(lane >> 1) + (lane & 1)) * 16, gs = sb + SM_EL + f * 64 + (lane >> 1) * 4;
        auto ea_gather = [&](int tt) {
            if (tt + f < tend) {
                const uint32_t o = lds32(gs + tt * 64);
                cp_async16_z(gd + tt * 512, eb + (o & ~1u), (o & 1u) ? 0 : 16);
            }
            cp_commit();
        };
        ea_gather(t);
        const uint32_t la = sb + SM_LIST + g * 8;
        const uint32_t ea = sb + SM_EA + g * 32 + q * 8;
        Tile x0, x1, y0, y1;
        fetch(x0, la + t * 64, k);
        fetch(x1, la + t * 64 + 64, k);
        ea_gather(t + 4);
        k.w3[0] = lds128(sb + SM_W3F + f * 1024 + lane * 16);
        k.w3[1] = lds128(sb + SM_W3F + f * 1024 + 512 + lane * 16);
        k.id = lds128(sm + MI_ID + lane * 16);
        float qi[2][4], acc[2][4];
        {
            const uint2 r = lds64(sm + MI_PERM + wg * 32 + q * 8);
            load_q(qi, sb, r.x, r.y, f, g);
        }
#pragma unroll
        for (int i = 0; i < 8; i++) (&acc[0][0])[i] = 0.f;
        auto group_switch = [&]() {
            flush_agg(tile_addr(sb + SM_AGG, lds32(sm + MI_PERM + wg * 32 + g * 4), 4 * f + q), acc);
            const uint2 r = lds64(sm + MI_PERM + (9 - wg) * 32 + q * 8);
            load_q(qi, sb, r.x, r.y, f, g);
#pragma unroll
            for (int i = 0; i < 8; i++) (&acc[0][0])[i] = 0.f;
        };
        auto tile = [&](const Tile& st) {
            if (t == tsw) group_switch();
            tile_mma(acc, st, ea + t * 512, qi, k);
            t++;
        };
        while (t < tend) {
            cp_wait<1>();
            bar_sync(7 + wg, 128);
            ea_gather(t + 8);
            validate(x0, x1, la + t * 64, k);
            fetch(y0, la + t * 64 + 128, k);
            fetch(y1, la + t * 64 + 192, k);
            tile(x0);
            if (t >= tend) break;
            tile(x1);
            if (t >= tend) break;
            validate(y0, y1, la + t * 64, k);
            fetch(x0, la + t * 64 + 128, k);
            fetch(x1, la + t * 64 + 192, k);
            tile(y0);
            if (t >= tend) break;
            tile(y1);
        }
        cp_wait<0>();
        if (tend == tsw) group_switch();
        flush_agg(tile_addr(sb + SM_AGG, lds32(sm + MI_PERM + (9 - wg) * 32 + g * 4), 4 * f + q), acc);
    }
    if (lane == 0 && f == 0) STAMP(14 + wg);

    fence_async();
    if (wg < 2) {
        float acc[40];
        const uint64_t da = make_desc(sb + SM_W + wg * 16384);
        bar_sync(7 + wg, 128);
        wg_fence();
        {
            const uint64_t db = make_desc(sb + SM_XS);
#pragma unroll
            for (int ks = 0; ks < 8; ks++) wgmma_n80(acc, da + ks * 128, db + (ks >> 2) * 640 + (ks & 3) * 2, ks);
        }
        wg_commit();
        __syncthreads();
        if (tid == 0) STAMP(19);
        wg_fence();
        {
            const uint64_t db = make_desc(sb + SM_AGG);
#pragma unroll
            for (int ks = 0; ks < 8; ks++) wgmma_n80(acc, da + 2048 + ks * 128, db + (ks >> 2) * 640 + (ks & 3) * 2, 1);
        }
        wg_commit();
        wg_wait<0>();
        if (tid == 0) STAMP(20);
        const uint32_t ot = sb + SM_OUT + wg * 10240;
        {
            const int mi = lane >> 3, r = lane & 7;
            const uint32_t a = ot + ((mi >> 1) * 8 + r) * 128 + (((f * 2 + (mi & 1)) ^ r) << 4);
#pragma unroll
            for (int j = 0; j < 10; j += 2) {
                uint32_t v[4];
#pragma unroll
                for (int i = 0; i < 4; i++)
                    v[i] = pack_bf16(silu_half(0.5f * acc[4 * j + 2 * i]), silu_half(0.5f * acc[4 * j + 2 * i + 1]));
                stsm_x4_trans(a + j * 1024, v[0], v[1], v[2], v[3]);
            }
        }
        bar_sync(7 + wg, 128);
        {
            const int t2 = tid & 127, r = t2 >> 3, c8 = t2 & 7;
            const uint32_t a = ot + r * 128 + ((c8 ^ (r & 7)) << 4);
            __nv_bfloat16* op = out + (size_t)(cta * NPC + r) * D + wg * 64 + c8 * 8;
            const int lim = min(nloc, NPC);
            uint4 v[5];
#pragma unroll
            for (int p = 0; p < 5; p++) v[p] = lds128(a + p * 2048);
#pragma unroll
            for (int p = 0; p < 5; p++)
                if (r + 16 * p < lim) stg128(op + 16 * p * D, v[p]);
        }
        if (tid == 0) { gepoch[cta * 8] = tag; STAMP(21); }
    } else {
        __syncthreads();
    }
}

__global__ void fb_zero(int n) {
    for (int i = blockIdx.x * blockDim.x + threadIdx.x; i < n; i += gridDim.x * blockDim.x) g_aggf[i] = 0.f;
}
__global__ void fb_edge(const __nv_bfloat16* x, const __nv_bfloat16* e_attr, const int* src, const int* dst,
                        const __nv_bfloat16* w_msg, int E) {
    __shared__ float in[2 * D + DE];
    for (int e = blockIdx.x; e < E; e += gridDim.x) {
        int s = src[e], d = dst[e], c = threadIdx.x;
        __syncthreads();
        in[c] = __bfloat162float(x[(size_t)s * D + c]);
        in[D + c] = __bfloat162float(x[(size_t)d * D + c]);
        if (c < DE) in[2 * D + c] = __bfloat162float(e_attr[(size_t)e * DE + c]);
        __syncthreads();
        float a = 0.f;
        for (int k = 0; k < 2 * D + DE; k++) a = fmaf(in[k], __bfloat162float(w_msg[k * D + c]), a);
        atomicAdd(&g_aggf[(size_t)d * D + c], a / (1.f + __expf(-a)));
    }
}
__global__ void fb_node(const __nv_bfloat16* x, const __nv_bfloat16* w_upd, __nv_bfloat16* out, int N) {
    __shared__ float in[2 * D];
    for (int n = blockIdx.x; n < N; n += gridDim.x) {
        int c = threadIdx.x;
        __syncthreads();
        in[c] = __bfloat162float(x[(size_t)n * D + c]);
        in[D + c] = g_aggf[(size_t)n * D + c];
        __syncthreads();
        float a = 0.f;
        for (int k = 0; k < 2 * D; k++) a = fmaf(in[k], __bfloat162float(w_upd[k * D + c]), a);
        out[(size_t)n * D + c] = __float2bfloat16(a / (1.f + __expf(-a)));
    }
}

}

extern "C" void kernel_launch(void* const* d_in, const int* in_sizes, int n_in, void* d_out, int out_size) {
    const __nv_bfloat16* x = (const __nv_bfloat16*)d_in[0];
    const __nv_bfloat16* e_attr = (const __nv_bfloat16*)d_in[1];
    const int* src = (const int*)d_in[2];
    const int* dst = (const int*)d_in[3];
    const __nv_bfloat16* w_msg = (const __nv_bfloat16*)d_in[4];
    const __nv_bfloat16* w_upd = (const __nv_bfloat16*)d_in[5];
    __nv_bfloat16* out = (__nv_bfloat16*)d_out;
    const int N = in_sizes[0] / D, E = in_sizes[2];

    static int mode = -1;
    static void *pP = nullptr, *pSeg = nullptr, *pEp = nullptr;
    if (mode < 0) {
        int dev = 0, sms = 0, nb = 0;
        cudaGetDevice(&dev);
        cudaDeviceGetAttribute(&sms, cudaDevAttrMultiProcessorCount, dev);
        cudaError_t e = cudaFuncSetAttribute(mpnn_kernel, cudaFuncAttributeMaxDynamicSharedMemorySize, SM_ALLOC);
        if (e == cudaSuccess) e = cudaOccupancyMaxActiveBlocksPerMultiprocessor(&nb, mpnn_kernel, NT, SM_ALLOC);
        if (e == cudaSuccess) e = cudaGetSymbolAddress(&pP, g_P);
        if (e == cudaSuccess) e = cudaGetSymbolAddress(&pSeg, g_seg);
        if (e == cudaSuccess) e = cudaGetSymbolAddress(&pEp, g_epoch);
        mode = (e == cudaSuccess && nb >= 1 && sms >= G) ? 1 : 0;
        (void)cudaGetLastError();
    }
    if (mode == 1 && N <= NMAX && E <= EMAX && (E & 1) == 0) {
        mpnn_kernel<<<G, NT, SM_ALLOC, cudaStreamPerThread>>>(x, e_attr, src, dst, w_msg, w_upd, out, (__nv_bfloat16*)pP,
                                                              (uint32_t*)pSeg, (uint32_t*)pEp, N, E);
    } else {
        fb_zero<<<256, 256, 0, cudaStreamPerThread>>>(N * D);
        fb_edge<<<2048, D, 0, cudaStreamPerThread>>>(x, e_attr, src, dst, w_msg, E);
        fb_node<<<2048, D, 0, cudaStreamPerThread>>>(x, w_upd, out, N);
    }
}
```

```cpp
#include <cuda.h>
#include <cuda_runtime.h>
#include <cuda_bf16.h>
#include <stdint.h>

namespace {

constexpr int D = 128;
constexpr int DE = 16;
constexpr int G = 132;
constexpr int NPC = 76;
constexpr int ROWS = 80;
constexpr int EPC = 1216;
constexpr int NT = 640;
constexpr int NMAX = G * NPC;
constexpr int EMAX = G * EPC;
constexpr int SEGCAP = 32;

constexpr int NTILE = 120;
constexpr int SM_XS = 0;
constexpr int SM_W = 20480;
constexpr int SM_AGG = SM_W + 65536;
constexpr int EAROWS = 1536;
constexpr int SM_EA = SM_AGG + 20480;
constexpr int SM_OUT = SM_EA;
constexpr int SM_LIST = SM_EA + EAROWS * 32;
constexpr int TRASH = (NTILE + 4) * 16;
constexpr int SM_EL = SM_LIST + 8000;
constexpr int SM_EG = SM_EL + 8000;
constexpr int SM_W3F = SM_EG + 13312;
constexpr int SM_MISC = SM_W3F + 4096;
constexpr int SM_STG = SM_AGG;
constexpr int SM_TOTAL = SM_MISC + 3328;
constexpr int SM_ALLOC = SM_TOTAL + 1024;
constexpr int MI_SEG = 0;
constexpr int MI_SLOW = 544;
constexpr int MI_ECNT = 548;
constexpr int MI_KEY = 560;
constexpr int MI_MB = 3264;
constexpr int MI_PERM = 1088;
constexpr int MI_SKEY = 1408;
constexpr int MI_NREC = 1728;
constexpr int MI_ID = 2752;

constexpr uint32_t W_EMPTY = 0xFFFFFFFFu;
constexpr uint32_t T_EMPTY = 0x7FFFFFFFu;
constexpr uint32_t T_OVF = 0x7FFFBFFFu;
#define GBLIND 4
constexpr int SPIN_LIMIT = 1 << 20;

__device__ __align__(256) __nv_bfloat16 g_P[(NMAX + G) * D];
__device__ __align__(256) uint32_t g_seg[G * G * SEGCAP];
__device__ __align__(256) uint32_t g_epoch[64];
__device__ float g_aggf[4 * 1024 * 1024];
#define STAMP(i) do { } while (0)

__device__ __forceinline__ uint32_t smem_u32(const void* p) { return (uint32_t)__cvta_generic_to_shared(p); }
__device__ __forceinline__ void cp_async16(uint32_t dst, const void* src) {
    asm volatile("cp.async.cg.shared.global [%0], [%1], 16;" ::"r"(dst), "l"(src) : "memory");
}
__device__ __forceinline__ void cp_async16_z(uint32_t dst, const void* src, int bytes) {
    asm volatile("cp.async.cg.shared.global [%0], [%1], 16, %2;" ::"r"(dst), "l"(src), "r"(bytes) : "memory");
}
__device__ __forceinline__ void cp_commit() { asm volatile("cp.async.commit_group;" ::: "memory"); }
template <int N> __device__ __forceinline__ void cp_wait() { asm volatile("cp.async.wait_group %0;" ::"n"(N) : "memory"); }
__device__ __forceinline__ void fence_async() { asm volatile("fence.proxy.async.shared::cta;" ::: "memory"); }
__device__ __forceinline__ void bar_sync(int id, int n) { asm volatile("bar.sync %0, %1;" ::"r"(id), "r"(n) : "memory"); }
__device__ __forceinline__ void bar_arrive(int id, int n) { asm volatile("bar.arrive %0, %1;" ::"r"(id), "r"(n) : "memory"); }
__device__ __forceinline__ uint32_t lds32(uint32_t a) { uint32_t v; asm volatile("ld.shared.u32 %0, [%1];" : "=r"(v) : "r"(a) : "memory"); return v; }
__device__ __forceinline__ uint2 lds64(uint32_t a) { uint2 v; asm volatile("ld.shared.v2.u32 {%0,%1}, [%2];" : "=r"(v.x), "=r"(v.y) : "r"(a) : "memory"); return v; }
__device__ __forceinline__ uint4 lds128(uint32_t a) { uint4 v; asm volatile("ld.shared.v4.u32 {%0,%1,%2,%3}, [%4];" : "=r"(v.x), "=r"(v.y), "=r"(v.z), "=r"(v.w) : "r"(a) : "memory"); return v; }
__device__ __forceinline__ void sts32(uint32_t a, uint32_t v) { asm volatile("st.shared.u32 [%0], %1;" ::"r"(a), "r"(v) : "memory"); }
__device__ __forceinline__ void sts128(uint32_t a, uint4 v) { asm volatile("st.shared.v4.u32 [%0], {%1,%2,%3,%4};" ::"r"(a), "r"(v.x), "r"(v.y), "r"(v.z), "r"(v.w) : "memory"); }
__device__ __forceinline__ void sts32_lt(uint32_t a, uint32_t v, uint32_t x, uint32_t lim) {
    asm volatile("{\n.reg .pred p;\nsetp.lt.u32 p, %2, %3;\n@p st.shared.u32 [%0], %1;\n}" ::"r"(a), "r"(v), "r"(x), "r"(lim) : "memory");
}
__device__ __forceinline__ void sts64_lt(uint32_t a, uint32_t v, uint32_t w, uint32_t x, uint32_t lim) {
    asm volatile("{\n.reg .pred p;\nsetp.lt.u32 p, %3, %4;\n@p st.shared.v2.u32 [%0], {%1, %2};\n}" ::"r"(a), "r"(v), "r"(w), "r"(x), "r"(lim) : "memory");
}
__device__ __forceinline__ void cp_async16_lt(uint32_t dst, const void* src, int x, int lim) {
    asm volatile("{\n.reg .pred p;\nsetp.lt.s32 p, %2, %3;\n@p cp.async.cg.shared.global [%0], [%1], 16;\n}" ::"r"(dst), "l"(src), "r"(x), "r"(lim) : "memory");
}
__device__ __forceinline__ uint32_t atoms_add_lt(uint32_t a, int d, uint32_t x, uint32_t lim) {
    uint32_t v = 0;
    asm volatile("{\n.reg .pred p;\nsetp.lt.u32 p, %3, %4;\n@p atom.shared.add.u32 %0, [%1], %2;\n}" : "+r"(v) : "r"(a), "r"(d), "r"(x), "r"(lim) : "memory");
    return v;
}
__device__ __forceinline__ uint32_t atoms_add(uint32_t a, int d) { uint32_t v; asm volatile("atom.shared.add.u32 %0, [%1], %2;" : "=r"(v) : "r"(a), "r"(d) : "memory"); return v; }
__device__ __forceinline__ uint4 ldg128(const void* p) { uint4 v; asm volatile("ld.global.v4.u32 {%0,%1,%2,%3}, [%4];" : "=r"(v.x), "=r"(v.y), "=r"(v.z), "=r"(v.w) : "l"(p) : "memory"); return v; }
__device__ __forceinline__ uint2 ldg64(const void* p) { uint2 v; asm volatile("ld.global.v2.u32 {%0,%1}, [%2];" : "=r"(v.x), "=r"(v.y) : "l"(p) : "memory"); return v; }
__device__ __forceinline__ void sts64(uint32_t a, uint32_t x, uint32_t y) { asm volatile("st.shared.v2.u32 [%0], {%1,%2};" ::"r"(a), "r"(x), "r"(y) : "memory"); }
__device__ __forceinline__ uint32_t ldg32(const void* p) { uint32_t v; asm volatile("ld.global.u32 %0, [%1];" : "=r"(v) : "l"(p) : "memory"); return v; }
__device__ __forceinline__ void stg128(void* p, uint4 v) { asm volatile("st.global.v4.u32 [%0], {%1,%2,%3,%4};" ::"l"(p), "r"(v.x), "r"(v.y), "r"(v.z), "r"(v.w) : "memory"); }
__device__ __forceinline__ uint32_t pack_bf16(float lo, float hi) {
    uint32_t r; asm("cvt.rn.bf16x2.f32 %0, %1, %2;" : "=r"(r) : "f"(hi), "f"(lo)); return r;
}
__device__ __forceinline__ float tanh_fast(float x) { float r; asm("tanh.approx.f32 %0, %1;" : "=f"(r) : "f"(x)); return r; }
__device__ __forceinline__ float silu_half(float h) { return fmaf(h, tanh_fast(h), h); }
__device__ __forceinline__ uint32_t movm(uint32_t a) { uint32_t d; asm volatile("movmatrix.sync.aligned.m8n8.trans.b16 %0, %1;" : "=r"(d) : "r"(a)); return d; }
__device__ __forceinline__ uint32_t shl_clamp(uint32_t v, uint32_t s) { uint32_t d; asm("shl.b32 %0, %1, %2;" : "=r"(d) : "r"(v), "r"(s)); return d; }
__device__ __forceinline__ void mma16(float (&d)[4], uint32_t a0, uint32_t a1, uint32_t a2, uint32_t a3, uint32_t b0, uint32_t b1) {
    asm("mma.sync.aligned.m16n8k16.row.col.f32.bf16.bf16.f32 {%0,%1,%2,%3}, {%4,%5,%6,%7}, {%8,%9}, {%0,%1,%2,%3};"
        : "+f"(d[0]), "+f"(d[1]), "+f"(d[2]), "+f"(d[3]) : "r"(a0), "r"(a1), "r"(a2), "r"(a3), "r"(b0), "r"(b1));
}
__device__ __forceinline__ void mma16_c(float (&d)[4], uint32_t a0, uint32_t a1, uint32_t a2, uint32_t a3, uint32_t b0, uint32_t b1, const float (&c)[4]) {
    asm("mma.sync.aligned.m16n8k16.row.col.f32.bf16.bf16.f32 {%0,%1,%2,%3}, {%4,%5,%6,%7}, {%8,%9}, {%10,%11,%12,%13};"
        : "=f"(d[0]), "=f"(d[1]), "=f"(d[2]), "=f"(d[3]) : "r"(a0), "r"(a1), "r"(a2), "r"(a3), "r"(b0), "r"(b1),
          "f"(c[0]), "f"(c[1]), "f"(c[2]), "f"(c[3]));
}
__device__ __forceinline__ void stsm_x4_trans(uint32_t addr, uint32_t r0, uint32_t r1, uint32_t r2, uint32_t r3) {
    asm volatile("stmatrix.sync.aligned.m8n8.x4.trans.shared.b16 [%0], {%1,%2,%3,%4};" ::"r"(addr), "r"(r0), "r"(r1), "r"(r2), "r"(r3) : "memory");
}

__device__ __forceinline__ uint64_t make_desc(uint32_t addr) {
    return (uint64_t)((addr & 0x3FFFF) >> 4) | ((uint64_t)64 << 16) | ((uint64_t)64 << 32) | ((uint64_t)1 << 62);
}
__device__ __forceinline__ void wg_fence() { asm volatile("wgmma.fence.sync.aligned;" ::: "memory"); }
__device__ __forceinline__ void wg_commit() { asm volatile("wgmma.commit_group.sync.aligned;" ::: "memory"); }
template <int N> __device__ __forceinline__ void wg_wait() { asm volatile("wgmma.wait_group.sync.aligned %0;" ::"n"(N) : "memory"); }
__device__ __forceinline__ void wgmma_n80(float (&d)[40], uint64_t da, uint64_t db, int scale_d) {
    asm volatile(
        "{\n.reg .pred p;\nsetp.ne.b32 p, %42, 0;\n"
        "wgmma.mma_async.sync.aligned.m64n80k16.f32.bf16.bf16 "
        "{%0,%1,%2,%3,%4,%5,%6,%7,%8,%9,%10,%11,%12,%13,%14,%15,%16,%17,%18,%19,"
        "%20,%21,%22,%23,%24,%25,%26,%27,%28,%29,%30,%31,%32,%33,%34,%35,%36,%37,%38,%39}, "
        "%40, %41, p, 1, 1, 1, 0;\n}\n"
        : "+f"(d[0]), "+f"(d[1]), "+f"(d[2]), "+f"(d[3]), "+f"(d[4]), "+f"(d[5]), "+f"(d[6]), "+f"(d[7]), "+f"(d[8]), "+f"(d[9]),
          "+f"(d[10]), "+f"(d[11]), "+f"(d[12]), "+f"(d[13]), "+f"(d[14]), "+f"(d[15]), "+f"(d[16]), "+f"(d[17]), "+f"(d[18]), "+f"(d[19]),
          "+f"(d[20]), "+f"(d[21]), "+f"(d[22]), "+f"(d[23]), "+f"(d[24]), "+f"(d[25]), "+f"(d[26]), "+f"(d[27]), "+f"(d[28]), "+f"(d[29]),
          "+f"(d[30]), "+f"(d[31]), "+f"(d[32]), "+f"(d[33]), "+f"(d[34]), "+f"(d[35]), "+f"(d[36]), "+f"(d[37]), "+f"(d[38]), "+f"(d[39])
        : "l"(da), "l"(db), "r"(scale_d));
}

__device__ __forceinline__ void wgmma_n40(float (&d)[20], uint64_t da, uint64_t db, int scale_d) {
    asm volatile(
        "{\n.reg .pred p;\nsetp.ne.b32 p, %22, 0;\n"
        "wgmma.mma_async.sync.aligned.m64n40k16.f32.bf16.bf16 "
        "{%0,%1,%2,%3,%4,%5,%6,%7,%8,%9,%10,%11,%12,%13,%14,%15,%16,%17,%18,%19}, "
        "%20, %21, p, 1, 1, 1, 0;\n}\n"
        : "+f"(d[0]), "+f"(d[1]), "+f"(d[2]), "+f"(d[3]), "+f"(d[4]), "+f"(d[5]), "+f"(d[6]), "+f"(d[7]), "+f"(d[8]), "+f"(d[9]),
          "+f"(d[10]), "+f"(d[11]), "+f"(d[12]), "+f"(d[13]), "+f"(d[14]), "+f"(d[15]), "+f"(d[16]), "+f"(d[17]), "+f"(d[18]), "+f"(d[19])
        : "l"(da), "l"(db), "r"(scale_d));
}
__device__ __forceinline__ void stsm_x2_trans(uint32_t addr, uint32_t r0, uint32_t r1) {
    asm volatile("stmatrix.sync.aligned.m8n8.x2.trans.shared.b16 [%0], {%1,%2};" ::"r"(addr), "r"(r0), "r"(r1) : "memory");
}
__device__ __forceinline__ uint4 ldg128_rlx(const void* p) { uint4 v; asm volatile("ld.relaxed.gpu.global.v4.u32 {%0,%1,%2,%3}, [%4];" : "=r"(v.x), "=r"(v.y), "=r"(v.z), "=r"(v.w) : "l"(p) : "memory"); return v; }
__device__ __forceinline__ void stg128_rlx(void* p, uint4 v) { asm volatile("st.relaxed.gpu.global.v4.u32 [%0], {%1,%2,%3,%4};" ::"l"(p), "r"(v.x), "r"(v.y), "r"(v.z), "r"(v.w) : "memory"); }

__device__ __forceinline__ uint32_t ldg32_rlx(const void* p) { uint32_t v; asm volatile("ld.relaxed.gpu.global.u32 %0, [%1];" : "=r"(v) : "l"(p) : "memory"); return v; }
__device__ __forceinline__ void hint_arrive(uint32_t* p) { asm volatile("red.relaxed.gpu.global.add.u32 [%0], 1;" ::"l"(p) : "memory"); }
__device__ __forceinline__ void hint_wait(const uint32_t* p, uint32_t target) {
    for (int it = 0; it < SPIN_LIMIT; it++) {
        uint32_t v;
        asm volatile("ld.relaxed.gpu.global.u32 %0, [%1];" : "=r"(v) : "l"(p) : "memory");
        if ((int)(v - target) >= 0) break;
    }
}

__host__ __device__ constexpr int boundary(int k) { return k == 0 ? 8 : 24 + 21 * k; }
__device__ __forceinline__ uint32_t tile_addr(uint32_t base, int row, int c) {
    return base + (c >> 3) * 10240 + row * 128 + (((c & 7) ^ (row & 7)) << 4);
}

__device__ __forceinline__ uint32_t split_cap(uint32_t sm) {
    const int d0 = lds32(sm + MI_SKEY) >> 7, d4 = lds32(sm + MI_SKEY + 16) >> 7, d72 = lds32(sm + MI_SKEY + 288) >> 7;
    return (max(d4, d0 - ((d72 + 1) & ~1)) + 1) & ~1;
}

struct Tile { uint4 p0, p1; };
struct Consts { uint4 w3[2]; uint4 id; uint32_t par, q8; const unsigned char* pb; };

__device__ __forceinline__ void fetch(Tile& st, uint32_t la, const Consts& k) {
    uint2 e = lds64(la);
    st.p0 = ldg128_rlx(k.pb + (size_t)e.x * 256);
    st.p1 = ldg128_rlx(k.pb + (size_t)e.y * 256);
}
__device__ __forceinline__ void fetch2(Tile& a, Tile& b, uint32_t la, const Consts& k) {
    const uint2 e = lds64(la), h = lds64(la + 64);
    a.p0 = ldg128_rlx(k.pb + (size_t)e.x * 256);
    a.p1 = ldg128_rlx(k.pb + (size_t)e.y * 256);
    b.p0 = ldg128_rlx(k.pb + (size_t)h.x * 256);
    b.p1 = ldg128_rlx(k.pb + (size_t)h.y * 256);
}
__device__ __forceinline__ bool stale(const Tile& a, const Tile& b, const Consts& k) {
    uint32_t t, u;
    asm("lop3.b32 %0, %1, %2, %3, 0x7E;" : "=r"(t) : "r"(a.p0.x), "r"(a.p1.x), "r"(k.par));
    asm("lop3.b32 %0, %1, %2, %3, 0x7E;" : "=r"(u) : "r"(b.p0.x), "r"(b.p1.x), "r"(k.par));
    asm("lop3.b32 %0, %1, %2, 1, 0xA8;" : "=r"(t) : "r"(t), "r"(u));
    return __any_sync(0xffffffffu, t != 0);
}
__device__ __forceinline__ void validate(Tile& a, Tile& b, uint32_t la, const Consts& k) {
    if (__builtin_expect(stale(a, b, k), 0)) {
#pragma unroll 1
        for (int it = 0; it < SPIN_LIMIT; it++) {
            fetch(a, la, k);
            fetch(b, la + 64, k);
            if (!stale(a, b, k)) break;
        }
    }
}
__device__ __forceinline__ void tile_mma(float (&acc)[2][4], const Tile& st, uint2 eo, const float (&qi)[2][4], const Consts& k) {
    const uint2 ea0 = lds64(eo.x | k.q8), ea1 = lds64(eo.y | k.q8);
    float c[2][2][4];
#pragma unroll
    for (int u = 0; u < 2; u++) {
        mma16_c(c[u][0], k.id.x, k.id.y, k.id.z, k.id.w, u ? st.p0.z : st.p0.x, u ? st.p0.w : st.p0.y, qi[u]);
        mma16_c(c[u][1], k.id.x, k.id.y, k.id.z, k.id.w, u ? st.p1.z : st.p1.x, u ? st.p1.w : st.p1.y, qi[u]);
    }
#pragma unroll
    for (int u = 0; u < 2; u++) {
        mma16(c[u][0], k.w3[u].x, k.w3[u].y, k.w3[u].z, k.w3[u].w, ea0.x, ea0.y);
        mma16(c[u][1], k.w3[u].x, k.w3[u].y, k.w3[u].z, k.w3[u].w, ea1.x, ea1.y);
    }
#pragma unroll
    for (int u = 0; u < 2; u++)
#pragma unroll
        for (int n = 0; n < 2; n++)
#pragma unroll
            for (int i = 0; i < 4; i++) acc[u][i] += silu_half(c[u][n][i]);
}
__device__ __forceinline__ void load_q(float (&qi)[2][4], uint32_t sb, int ra, int rb, int f, int g) {
    const uint4 a = lds128(tile_addr(sb + SM_AGG, ra, 4 * f + (g >> 1))), b = lds128(tile_addr(sb + SM_AGG, rb, 4 * f + (g >> 1)));
    const uint32_t sel = (g & 1) ? 0x3244u : 0x1044u;
    qi[0][0] = 0.5f * __uint_as_float(__byte_perm(a.x, 0, sel)); qi[0][1] = 0.5f * __uint_as_float(__byte_perm(b.x, 0, sel));
    qi[0][2] = 0.5f * __uint_as_float(__byte_perm(a.y, 0, sel)); qi[0][3] = 0.5f * __uint_as_float(__byte_perm(b.y, 0, sel));
    qi[1][0] = 0.5f * __uint_as_float(__byte_perm(a.z, 0, sel)); qi[1][1] = 0.5f * __uint_as_float(__byte_perm(b.z, 0, sel));
    qi[1][2] = 0.5f * __uint_as_float(__byte_perm(a.w, 0, sel)); qi[1][3] = 0.5f * __uint_as_float(__byte_perm(b.w, 0, sel));
}
__device__ __forceinline__ void flush_agg(uint32_t addr, const float (&acc)[2][4]) {
    uint4 v;
    v.x = movm(pack_bf16(acc[0][0], acc[0][1]));
    v.y = movm(pack_bf16(acc[0][2], acc[0][3]));
    v.z = movm(pack_bf16(acc[1][0], acc[1][1]));
    v.w = movm(pack_bf16(acc[1][2], acc[1][3]));
    sts128(addr, v);
}

__device__ __forceinline__ void tma_load(uint32_t dst, const CUtensorMap* tm, int c0, int c1, uint32_t mbar) {
    asm volatile("cp.async.bulk.tensor.2d.shared::cluster.global.mbarrier::complete_tx::bytes [%0], [%1, {%2, %3}], [%4];"
                 ::"r"(dst), "l"(tm), "r"(c0), "r"(c1), "r"(mbar) : "memory");
}
__device__ __forceinline__ void tma_store(const CUtensorMap* tm, int c0, int c1, uint32_t src) {
    asm volatile("cp.async.bulk.tensor.2d.global.shared::cta.bulk_group [%0, {%1, %2}], [%3];" ::"l"(tm), "r"(c0), "r"(c1), "r"(src) : "memory");
    asm volatile("cp.async.bulk.commit_group;" ::: "memory");
}
__device__ __forceinline__ void tma_store_wait() { asm volatile("cp.async.bulk.wait_group.read 0;" ::: "memory"); }
__device__ __forceinline__ void mbar_wait0(uint32_t a) {
    for (int it = 0; it < SPIN_LIMIT; it++) {
        uint32_t ok;
        asm volatile("{\n.reg .pred p;\nmbarrier.try_wait.parity.shared::cta.b64 p, [%1], 0;\nselp.u32 %0, 1, 0, p;\n}" : "=r"(ok) : "r"(a) : "memory");
        if (ok) break;
    }
}

__device__ __noinline__ void slow_path(uint32_t sb, const __nv_bfloat16* e_attr, const int* src, const int* dst, int E, Consts k) {
    const int tid = threadIdx.x, lane = tid & 31, wg = tid >> 7, f = (tid >> 5) & 3, g = lane >> 2, q = lane & 3, cta = blockIdx.x;
    const uint32_t s_deg = sb + SM_MISC + MI_KEY;
    float acc[2][2][4];
    for (int i = 0; i < 16; i++) (&acc[0][0][0])[i] = 0.f;
    int scan = 0, state = 0, row = 0;
    bool more = true;
    while (more) {
        more = false;
        __syncthreads();
        if (tid < ROWS) sts32(s_deg + tid * 4, 0);
        for (int i = tid; i < EAROWS * 2; i += NT) sts128(sb + SM_EA + i * 16, make_uint4(0, 0, 0, 0));
        for (int i = tid; i < (NTILE + 4) * 16; i += NT) sts32(sb + SM_LIST + i * 4, NMAX + cta);
        __syncthreads();
        while (true) {
            const int e = scan + tid;
            if (state == 0) {
                state = 2;
                if (e < E) {
                    int dn = dst[e];
                    if (dn / NPC == cta) { state = 1; row = dn - cta * NPC; }
                }
            }
            if (state == 1) {
                uint32_t rank = atoms_add(s_deg + row * 4, 1);
                if (rank < 18) {
                    uint32_t pos = ((row >> 3) * 9 + (rank >> 1)) * 16 + (row & 7) * 2 + (rank & 1);
                    sts32(sb + SM_LIST + pos * 4, (uint32_t)src[e]);
                    sts128(sb + SM_EA + pos * 32, ldg128(e_attr + (size_t)e * DE));
                    sts128(sb + SM_EA + pos * 32 + 16, ldg128(e_attr + (size_t)e * DE + 8));
                    state = 2;
                }
            }
            if (__syncthreads_or(state == 1)) { more = true; break; }
            scan += NT;
            state = 0;
            if (scan >= E) break;
        }
#pragma unroll
        for (int b = 0; b < 2; b++) {
            const int grp = 2 * wg + b;
            const int mx = min((int)__reduce_max_sync(0xffffffffu, lds32(s_deg + (grp * 8 + g) * 4)), 18);
            float qi[2][4];
            load_q(qi, sb, grp * 8 + 2 * q, grp * 8 + 2 * q + 1, f, g);
            for (int t = 0; t * 2 < mx; t++) {
                const int tile = grp * 9 + t;
                Tile st, s2;
                const uint32_t la = sb + SM_LIST + tile * 64 + g * 8;
                fetch(st, la, k);
                fetch(s2, la + 64, k);
                validate(st, s2, la, k);
                tile_mma(acc[b], st, make_uint2(sb + SM_EA + tile * 512 + g * 64, sb + SM_EA + tile * 512 + g * 64 + 32), qi, k);
            }
        }
    }
    __syncwarp();
    flush_agg(tile_addr(sb + SM_AGG, wg * 16 + g, 4 * f + q), acc[0]);
    flush_agg(tile_addr(sb + SM_AGG, wg * 16 + 8 + g, 4 * f + q), acc[1]);
}

__global__ void __launch_bounds__(NT, 1)
mpnn_kernel(const __nv_bfloat16* __restrict__ e_attr, const int* __restrict__ src, const int* __restrict__ dst,
            const __nv_bfloat16* __restrict__ w_msg, const __nv_bfloat16* __restrict__ w_upd,
            __nv_bfloat16* __restrict__ out, __nv_bfloat16* __restrict__ gP, uint32_t* __restrict__ gseg,
            uint32_t* __restrict__ gepoch, int N, int E,
            const __grid_constant__ CUtensorMap tm_x, const __grid_constant__ CUtensorMap tm_wm,
            const __grid_constant__ CUtensorMap tm_wu, const __grid_constant__ CUtensorMap tm_p) {
    extern __shared__ unsigned char smem_raw[];
    const uint32_t sb = (smem_u32(smem_raw) + 1023u) & ~1023u;
    const int tid = threadIdx.x, warp = tid >> 5, lane = tid & 31;
    const int wg = warp >> 2, f = warp & 3, g = lane >> 2, q = lane & 3;
    const int cta = blockIdx.x;
    const int wgu = (int)__reduce_max_sync(0xffffffffu, (uint32_t)wg);
    const uint32_t sm = sb + SM_MISC;
    if (tid == 0) STAMP(0);

    uint2 d2 = make_uint2(~0u, 0), s2;
    {
        const int e0 = ((tid >> 4) * G + cta) * 32 + (tid & 15) * 2;
        if (tid < EPC / 2 && e0 < E) {
            d2 = ldg64(dst + e0);
            s2 = ldg64(src + e0);
        }
    }
    const uint32_t tag = ldg32_rlx(gepoch) / G + 1;
    sts128(sb + SM_STG + tid * 16, make_uint4(W_EMPTY, W_EMPTY, W_EMPTY, W_EMPTY));
    if (tid < 416) sts128(sb + SM_STG + 10240 + tid * 16, make_uint4(W_EMPTY, W_EMPTY, W_EMPTY, W_EMPTY));
    else if (tid < 636) sts32(sm + (tid - 416) * 4, tid >= 556 ? 127 - (tid - 556) : tid == 553);
    if (warp == 19) {
        if (lane == 31) {
            asm volatile("mbarrier.init.shared::cta.b64 [%0], 1;" ::"r"(sm + MI_MB) : "memory");
            asm volatile("mbarrier.init.shared::cta.b64 [%0], 1;" ::"r"(sm + MI_MB + 8) : "memory");
            asm volatile("mbarrier.init.shared::cta.b64 [%0], 96;" ::"r"(sm + MI_MB + 16) : "memory");
            asm volatile("mbarrier.init.shared::cta.b64 [%0], 96;" ::"r"(sm + MI_MB + 24) : "memory");
            sts64(sm + MI_NREC + 127 * 8, 0x40000000u, 0u);
        }
        __syncwarp();
        bar_arrive(3, 640);
        if (lane == 31) {
            fence_async();
            asm volatile("mbarrier.arrive.expect_tx.shared::cta.b64 _, [%0], %1;" ::"r"(sm + MI_MB), "r"(20480 + 65536) : "memory");
            asm volatile("mbarrier.arrive.expect_tx.shared::cta.b64 _, [%0], %1;" ::"r"(sm + MI_MB + 8), "r"(65536) : "memory");
#pragma unroll
            for (int b = 0; b < 4; b++) tma_load(sb + SM_W + b * 16384, &tm_wm, (b & 1) * 64, (b >> 1) * 128, sm + MI_MB);
            tma_load(sb + SM_XS, &tm_x, 0, cta * NPC, sm + MI_MB);
            tma_load(sb + SM_XS + 10240, &tm_x, 64, cta * NPC, sm + MI_MB);
            asm volatile("prefetch.tensormap [%0];" ::"l"(&tm_p) : "memory");
            asm volatile("prefetch.tensormap [%0];" ::"l"(&tm_wu) : "memory");
        }
        __syncwarp();
    } else {
        bar_sync(3, 640);
    }
    if (tid == 0) STAMP(23);
    uint32_t w3raw[16];
    if (wg == 4) {
        if (tid >= 636)
            asm volatile("prefetch.global.L2 [%0];" ::"l"(reinterpret_cast<const unsigned char*>(w_upd) + min(cta * 4 + (tid - 636), 511) * 128));
        const unsigned short* w3p = reinterpret_cast<const unsigned short*>(w_msg + 2 * D * D) + 4 * q * D + 32 * f + (g >> 1) * 8 + (g & 1);
#pragma unroll
        for (int i = 0; i < 16; i++) {
            const int u = i >> 3, r = (i >> 1) & 3, o = 4 * u + 2 * (r & 1) + (2 * (r >> 1) + (i & 1)) * D;
            unsigned short v;
            asm volatile("ld.global.nc.u16 %0, [%1];" : "=h"(v) : "l"(w3p + o));
            w3raw[i] = v;
        }
    }
    if (d2.x != ~0u) {
        const uint32_t dc0 = d2.x / NPC, dc1 = d2.y / NPC;
        const uint32_t r0 = atoms_add(sm + MI_SEG + dc0 * 4, 1), r1 = atoms_add(sm + MI_SEG + dc1 * 4, 1);
        const uint32_t w0 = s2.x | (((tid << 8) + d2.x - dc0 * NPC) << 14), w1 = s2.y | (((tid << 8) + 128 + d2.y - dc1 * NPC) << 14);
        sts32_lt(sb + SM_STG + dc0 * 128 + (r0 & 7) * 16 + (r0 >> 3) * 4, w0, r0, SEGCAP);
        sts32_lt(sb + SM_STG + dc1 * 128 + (r1 & 7) * 16 + (r1 >> 3) * 4, w1, r1, SEGCAP);
    }
    if (tid == 0) STAMP(24);
    __syncthreads();
    const uint32_t parw = tag << 31;
    {
        uint4 v[2];
        uint32_t cn[2];
#pragma unroll
        for (int i = 0; i < 2; i++) {
            v[i] = lds128(sb + SM_STG + tid * 16 + i * 10240);
            cn[i] = lds32(sm + MI_SEG + min((tid >> 3) + i * 80, 135) * 4);
        }
#pragma unroll
        for (int i = 0; i < 2; i++) {
            uint32_t tl = T_EMPTY;
            if (cn[i] > 24) {
                const uint32_t w = v[i].w;
                if (w != W_EMPTY) tl = (((w >> 21) * ROWS + ((w >> 14) & 127u)) << 14) | (w & 16383u);
                if (cn[i] > SEGCAP) tl = T_OVF;
            }
            v[i].w = tl | parw;
            if (i == 0 || tid < 416) stg128_rlx(gseg + (size_t)cta * (G * SEGCAP) + tid * 4 + i * 2560, v[i]);
        }
    }
    const uint32_t* bp = gseg + ((size_t)(tid >> 3) * G + cta) * SEGCAP + (tid & 7) * 4;
    uint4 v0, v1 = make_uint4(W_EMPTY, W_EMPTY, W_EMPTY, T_EMPTY | parw);
    auto prefill2 = [&]() {
        const uint32_t pr = NMAX + cta;
        if (tid < 496) sts128(sb + SM_LIST + tid * 16, make_uint4(pr, pr, pr, pr));
        if (tid >= 144) sts128(sb + SM_EL + (tid - 144) * 16, make_uint4(sb + SM_EA, sb + SM_EA, sb + SM_EA, sb + SM_EA));
        else if (tid >= 142) sts128(sb + SM_EA + (tid - 142) * 16, make_uint4(0, 0, 0, 0));
        else if (tid < 32) {
            uint32_t idf = shl_clamp(0x3F00u, (uint32_t)((g - 2 * q) << 4));
            sts128(sm + MI_ID + lane * 16, make_uint4(idf, 0, 0, idf));
        }
    };
    if (wg < 4) {
        bar_arrive(2, 640);
        prefill2();
        mbar_wait0(sm + MI_MB);
        if (tid == 0) STAMP(1);
#define PFN 1
#define PFS 1
        if (tid >= 512 - PFN) {
            int eb = ((cta + (511 - tid) * PFS) % G) * EPC, ne = min(EPC, E - eb);
            if (ne > 0) asm volatile("cp.async.bulk.prefetch.L2.global [%0], %1;" ::"l"(e_attr + (size_t)eb * DE), "r"(ne * 32) : "memory");
        }
        float gacc[40];
        const uint64_t da = make_desc(sb + SM_W + wgu * 16384), db = make_desc(sb + SM_XS);
        wg_fence();
#pragma unroll
        for (int ks = 0; ks < 8; ks++) wgmma_n80(gacc, da + ks * 128, db + (ks >> 2) * 640 + (ks & 3) * 2, ks);
        wg_commit();
        bar_sync(4, 640);
        if (tid == 0) STAMP(22);
        v0 = ldg128_rlx(bp);
        v1 = ldg128_rlx(bp + (size_t)68 * G * SEGCAP);
        const uint32_t so = (wg < 2 ? sb + SM_W + wg * 16384 : sb + SM_AGG + (wg - 2) * 10240) +
                            (((lane >> 4) & 1) * 8 + (lane & 7)) * 128 + (((f * 2 + ((lane >> 3) & 1)) ^ (lane & 7)) << 4);
        const bool pm = wg < 2 && g == 0;
        const uint32_t keep = pm ? 0xFFFEFFFEu : 0xFFFFFFFFu, setb = pm ? (tag & 1u) * 0x10001u : 0u;
        wg_wait<0>();
        if (tid == 0) STAMP(2);
        if (wg < 2) bar_sync(7 + wg, 128);
#pragma unroll
        for (int j = 0; j < 5; j++)
            stsm_x4_trans(so + j * 2048,
                          (pack_bf16(gacc[8 * j], gacc[8 * j + 1]) & keep) | setb, (pack_bf16(gacc[8 * j + 2], gacc[8 * j + 3]) & keep) | setb,
                          (pack_bf16(gacc[8 * j + 4], gacc[8 * j + 5]) & keep) | setb, (pack_bf16(gacc[8 * j + 6], gacc[8 * j + 7]) & keep) | setb);
        if (wg < 2) fence_async();
        bar_arrive(5, 544);
    } else {
        bar_sync(2, 640);
        if (tid == 512) { STAMP(4); hint_arrive(gepoch); }
        prefill2();
        uint32_t w[8];
#pragma unroll
        for (int i = 0; i < 8; i++)
            asm("mul.bf16x2 %0, %1, %2;" : "=r"(w[i]) : "r"(w3raw[2 * i] | (w3raw[2 * i + 1] << 16)), "r"(0x3F003F00u));
        sts128(sb + SM_W3F + f * 1024 + lane * 16, make_uint4(w[0], w[1], w[2], w[3]));
        sts128(sb + SM_W3F + f * 1024 + 512 + lane * 16, make_uint4(w[4], w[5], w[6], w[7]));
        if (tid >= 624)
            stg128_rlx(gP + (size_t)(NMAX + cta) * D + (tid - 624) * 8, make_uint4(0xFF00FF00u | (tag & 1u), 0xFF00FF00u, 0xFF00FF00u, 0xFF00FF00u));
        if (tid == 512) { hint_wait(gepoch, tag * G); STAMP(7); }
        __syncwarp();
        bar_sync(4, 640);
        if (warp == 16) v0 = ldg128_rlx(bp);
    }
    if (warp >= 17) {
        if (warp == 17) {
            bar_sync(5, 544);
            if (lane == 0) {
                tma_store(&tm_p, 0, cta * NPC, sb + SM_W);
                tma_store(&tm_p, 64, cta * NPC, sb + SM_W + 16384);
                tma_load(sb + SM_W + 32768, &tm_wu, 0, 128, sm + MI_MB + 8);
                tma_load(sb + SM_W + 49152, &tm_wu, 64, 128, sm + MI_MB + 8);
                STAMP(3);
            }
            __syncwarp();
        }
        bar_sync(6, 640);
        const int n = min((int)lds32(sm + MI_ECNT), EAROWS);
        const unsigned char* geb = reinterpret_cast<const unsigned char*>(e_attr) + (lane & 1) * 16;
        const int n0 = lds32(sm + MI_SLOW) == 0 ? n : 0;
        const int r0 = 1 + (lane >> 1) + (warp - 17) * 32;
#pragma unroll
        for (int it = 0; it < GBLIND; it++)
#pragma unroll
            for (int j = 0; j < 2; j++) {
                const int r = r0 + it * 96 + j * 16;
                cp_async16_lt(sb + SM_EA + r * 32 + (lane & 1) * 16, geb + lds32(sb + SM_EG + r * 8), r, n0);
            }
        constexpr int GR = 20;
        uint2 rc[GR];
#pragma unroll
        for (int j = 0; j < GR; j++) rc[j] = lds64(sb + SM_EG + (r0 + (GBLIND + (j >> 1)) * 96 + (j & 1) * 16) * 8);
#pragma unroll 1
        for (int r = r0 + (GBLIND + GR / 2) * 96; r < n0 + 16; r += 96) {
            cp_async16_lt(sb + SM_EA + r * 32 + (lane & 1) * 16, geb + lds32(sb + SM_EG + r * 8), r, n0);
            cp_async16_lt(sb + SM_EA + r * 32 + 512 + (lane & 1) * 16, geb + lds32(sb + SM_EG + r * 8 + 128), r + 16, n0);
        }
        bar_sync(10, 640);
#pragma unroll
        for (int j = 0; j < GR; j++) rc[j].y = lds32(sm + MI_NREC + 4 + ((rc[j].y >> 11) & 1016u));
#pragma unroll
        for (int ph = 0; ph < 2; ph++) {
#pragma unroll
            for (int j = 0; j < GR; j++) {
                const int r = r0 + (GBLIND + (j >> 1)) * 96 + (j & 1) * 16;
                cp_async16_lt(sb + SM_EA + r * 32 + (lane & 1) * 16, geb + rc[j].x, ((rc[j].y != 0u) == (ph == 0)) ? r : n0, n0);
            }
            asm volatile("cp.async.mbarrier.arrive.noinc.shared::cta.b64 [%0];" ::"r"(sm + MI_MB + 24 - ph * 8) : "memory");
            if (ph == 0 && tid == 544) STAMP(10);
        }
        if (tid == 544) {
            STAMP(12);
            tma_store_wait();
            tma_load(sb + SM_W, &tm_wu, 0, 0, sm + MI_MB + 8);
            tma_load(sb + SM_W + 16384, &tm_wu, 64, 0, sm + MI_MB + 8);
        }
        __syncwarp();
        bar_sync(11, 640);
    } else {
        __syncwarp();
#pragma unroll 1
        for (int it = 0; it < SPIN_LIMIT; it++) {
            if (!__any_sync(0xffffffffu, (int)((v0.w ^ parw) | (v1.w ^ parw)) < 0)) break;
            v0 = ldg128_rlx(bp);
            if (wg < 4) v1 = ldg128_rlx(bp + (size_t)68 * G * SEGCAP);
        }
        if (tid == 0) STAMP(8);
        const uint32_t lt = (1u << lane) - 1u;
        uint32_t en[8] = {v0.x, v1.x, v0.y, v1.y, v0.z, v1.z, W_EMPTY, W_EMPTY}, es[8], gb = 0;
        int gt = 0;
        auto count = [&](int i) {
            const uint32_t m = __ballot_sync(0xffffffffu, en[i] != W_EMPTY);
            es[i] = gt + __popc(m & lt);
            gt += __popc(m);
        };
        auto put = [&](int i) {
            const uint32_t el = en[i] >> 21;
            sts64_lt(sb + SM_EG + (gb + es[i]) * 8, (el + (el >> 5) * (G * 32 - 32) + ((tid >> 3) + (i & 1) * 68) * 32) * 32, en[i], en[i], W_EMPTY);
        };
#pragma unroll
        for (int i = 0; i < 6; i++) count(i);
        const bool deep = __any_sync(0xffffffffu, (v0.w & v1.w & T_EMPTY) != T_EMPTY);
        if (deep) {
#pragma unroll
            for (int r = 0; r < 2; r++) {
                const uint32_t tl = (r ? v1.w : v0.w) & T_EMPTY, er = tl >> 14, el = ((er >> 4) * 52429u) >> 18;
                if (tl == T_OVF) sts32(sm + MI_SLOW, 1);
                if (tl < T_OVF) en[6 + r] = (el << 21) | ((er - el * ROWS) << 14) | (tl & 16383u);
                count(6 + r);
            }
        }
        if (lane == 0) gb = atoms_add(sm + MI_ECNT, gt);
        gb = __shfl_sync(0xffffffffu, gb, 0);
        if (gb + gt > EAROWS || gt > 128) { sts32(sm + MI_SLOW, 1); gb = 0; gt = 0; }
#pragma unroll
        for (int i = 0; i < 6; i++) put(i);
        if (deep) { put(6); put(7); }
        __syncwarp();
        bar_arrive(6, 640);
        uint32_t rec[4], rk[4];
#pragma unroll
        for (int j = 0; j < 4; j++) rec[j] = lds32(sb + SM_EG + (gb + lane) * 8 + 4 + j * 256);
#pragma unroll
        for (int j = 0; j < 4; j++) {
            if (lane + 32 * j >= gt) rec[j] = W_EMPTY;
            rk[j] = 0;
            if (32 * j < gt) rk[j] = atoms_add_lt(sm + MI_KEY + ((rec[j] >> 12) & 508u), 128, rec[j], W_EMPTY);
        }
        bar_sync(9, 544);
        if (tid == 0) STAMP(9);
        if (warp < 10) {
            const uint32_t key = lds32(sm + MI_KEY + (tid >> 2) * 4);
            uint4 o[5];
#pragma unroll
            for (int i = 0; i < 5; i++) o[i] = lds128(sm + MI_KEY + (tid & 3) * 80 + i * 16);
            uint32_t sp = 0, sq = 0;
#pragma unroll
            for (int i = 0; i < 5; i++) {
                sp += (key - o[i].x) >> 31; sq += (key - o[i].y) >> 31;
                sp += (key - o[i].z) >> 31; sq += (key - o[i].w) >> 31;
            }
            sp += sq;
            sp += __shfl_xor_sync(0xffffffffu, sp, 1);
            sp += __shfl_xor_sync(0xffffffffu, sp, 2);
            int grp = sp >> 3;
            grp = grp == 0 ? 9 : grp == 9 ? 0 : grp;
            const bool down = grp < 5;
            const uint32_t tp = grp * 8 + (sp & 7);
            sts32_lt(sm + MI_PERM + tp * 4, tid >> 2, tid & 3, 1);
            sts32_lt(sm + MI_SKEY + sp * 4, key, tid & 3, 1);
            sts64_lt(sm + MI_NREC + tid * 2, boundary(down ? grp : 9 - grp) * 16 + (sp & 7) * 2 + (down ? -14 : 0),
                     down ? ~0u : sp < 4 ? 1u : 0u, tid & 3, 1);
        }
        bar_arrive(10, 640);
        bar_sync(9, 544);
        if (tid == 0) STAMP(25);
        {
            uint2 nr[4];
#pragma unroll
            for (int j = 0; j < 4; j++) nr[j] = lds64(sm + MI_NREC + ((rec[j] >> 11) & 1016u));
            const uint32_t cap = split_cap(sm) << 7;
#pragma unroll
            for (int j = 0; j < 4; j++) {
                if (nr[j].y == 1u) {
                    nr[j].y = 0u;
                    if (rk[j] >= cap) { rk[j] -= cap; nr[j].x -= 6; nr[j].y = ~0u; }
                }
                const uint32_t off = ((rk[j] >> 4) & ~15u) | ((rk[j] >> 7) & 1u);
                const uint32_t ps = min(nr[j].x + (off ^ nr[j].y), (uint32_t)TRASH);
                sts32(sb + SM_LIST + ps * 4, rec[j] & 16383u);
                sts32(sb + SM_EL + ps * 4, sb + SM_EA + (gb + lane + 32 * j) * 32);
            }
        }
        if (tid == 0) STAMP(11);
        bar_arrive(11, 640);
        bar_sync(9, 544);
    }
    if (tid == 0) STAMP(13);

    Consts k;
    k.par = tag;
    k.q8 = q * 8;
    k.pb = reinterpret_cast<const unsigned char*>(gP) + f * 64 + q * 16;
    int nt;
    bool slow;
    {
        const int l = min(lane, 9);
        nt = (int)((lds32(sm + MI_SKEY + (l == 0 ? 9 : l) * 32) >> 7) + 1) >> 1;
        if (l == 9) nt = split_cap(sm) >> 1;
        const int other = __shfl_sync(0xffffffffu, nt, (10 - l) % 10);
        const int lim = l == 0 ? 16 : l == 5 ? 24 : (l == 1 || l == 9) ? 37 : 21;
        slow = __any_sync(0xffffffffu, nt + other > lim) || lds32(sm + MI_SLOW) != 0;
    }
    if (slow) {
        k.w3[0] = lds128(sb + SM_W3F + f * 1024 + lane * 16);
        k.w3[1] = lds128(sb + SM_W3F + f * 1024 + 512 + lane * 16);
        k.id = lds128(sm + MI_ID + lane * 16);
        mbar_wait0(sm + MI_MB + 16);
        slow_path(sb, e_attr, src, dst, E, k);
    } else {
        const int tsw = (int)__reduce_max_sync(0xffffffffu, (uint32_t)boundary(wg));
        int t = tsw - (int)__reduce_max_sync(0xffffffffu, lane == wg ? nt : 0);
        const int tend = tsw + (int)__reduce_max_sync(0xffffffffu, lane == 9 - wg ? nt : 0);
        const uint32_t la = sb + SM_LIST + g * 8;
        k.w3[0] = lds128(sb + SM_W3F + f * 1024 + lane * 16);
        k.w3[1] = lds128(sb + SM_W3F + f * 1024 + 512 + lane * 16);
        k.id = lds128(sm + MI_ID + lane * 16);
        float qi[2][4], acc[2][4];
        {
            const uint2 r = lds64(sm + MI_PERM + wg * 32 + q * 8 + ((wg == 0 && q >= 2) ? 272 : 0));
            load_q(qi, sb, r.x, r.y, f, g);
        }
#pragma unroll
        for (int i = 0; i < 8; i++) (&acc[0][0])[i] = 0.f;
        Tile x0, y0;
        fetch(x0, la + t * 64, k);
        uint2 en = lds64(la + t * 64 + 64), eo = lds64(la + (SM_EL - SM_LIST) + t * 64);
        auto group_switch = [&]() {
            flush_agg(tile_addr(sb + SM_AGG, lds32(sm + MI_PERM + wg * 32 + g * 4), 4 * f + q), acc);
            const uint2 r = lds64(sm + MI_PERM + (9 - wg) * 32 + q * 8);
            load_q(qi, sb, r.x, r.y, f, g);
#pragma unroll
            for (int i = 0; i < 8; i++) {
                const float v = __shfl_xor_sync(0xffffffffu, (&acc[0][0])[i], 2);
                (&acc[0][0])[i] = (wg == 0 && q < 2) ? v : 0.f;
            }
        };
        mbar_wait0(sm + MI_MB + 24);
        if (tid == 0) STAMP(27);
        if (t == tsw) mbar_wait0(sm + MI_MB + 16);
        uint2 ea0 = lds64(eo.x | k.q8), ea1 = lds64(eo.y | k.q8);
        eo = lds64(la + (SM_EL - SM_LIST) + t * 64 + 64);
        auto step = [&](Tile& st, Tile& nx) {
            if (t >= tsw - 1 && t <= tsw) {
                if (t == tsw) group_switch(); else mbar_wait0(sm + MI_MB + 16);
            }
            if (__builtin_expect(stale(st, st, k), 0)) {
#pragma unroll 1
                for (int it = 0; it < SPIN_LIMIT; it++) {
                    fetch(st, la + t * 64, k);
                    if (!stale(st, st, k)) break;
                }
            }
            nx.p0 = ldg128_rlx(k.pb + (size_t)en.x * 256);
            nx.p1 = ldg128_rlx(k.pb + (size_t)en.y * 256);
            float c[2][2][4];
#pragma unroll
            for (int u = 0; u < 2; u++) {
                mma16_c(c[u][0], k.id.x, k.id.y, k.id.z, k.id.w, u ? st.p0.z : st.p0.x, u ? st.p0.w : st.p0.y, qi[u]);
                mma16_c(c[u][1], k.id.x, k.id.y, k.id.z, k.id.w, u ? st.p1.z : st.p1.x, u ? st.p1.w : st.p1.y, qi[u]);
            }
#pragma unroll
            for (int u = 0; u < 2; u++) {
                mma16(c[u][0], k.w3[u].x, k.w3[u].y, k.w3[u].z, k.w3[u].w, ea0.x, ea0.y);
                mma16(c[u][1], k.w3[u].x, k.w3[u].y, k.w3[u].z, k.w3[u].w, ea1.x, ea1.y);
            }
            ea0 = lds64(eo.x | k.q8);
            ea1 = lds64(eo.y | k.q8);
            en = lds64(la + t * 64 + 128);
            eo = lds64(la + (SM_EL - SM_LIST) + t * 64 + 128);
#pragma unroll
            for (int u = 0; u < 2; u++)
#pragma unroll
                for (int n = 0; n < 2; n++)
#pragma unroll
                    for (int i = 0; i < 4; i++) acc[u][i] += silu_half(c[u][n][i]);
            t++;
        };
        while (t < tend) {
            step(x0, y0);
            if (t >= tend) break;
            step(y0, x0);
        }
        if (tend == tsw) group_switch();
        flush_agg(tile_addr(sb + SM_AGG, lds32(sm + MI_PERM + (9 - wg) * 32 + g * 4), 4 * f + q), acc);
    }
    if (lane == 0 && f == 0) STAMP(14 + wg);

    fence_async();
    if (wg == 0) { bar_arrive(14, 640); return; }
    {
        const int half = wgu < 3, h = (wgu - 1) & 1;
        float acc[20];
        const uint64_t da = make_desc(sb + SM_W + h * 16384);
        mbar_wait0(sm + MI_MB + 8);
        wg_fence();
        {
            const uint64_t db = make_desc(sb + SM_XS + half * 5120);
#pragma unroll
            for (int ks = 0; ks < 8; ks++) wgmma_n40(acc, da + ks * 128, db + (ks >> 2) * 640 + (ks & 3) * 2, ks);
        }
        wg_commit();
        bar_sync(14, 640);
        if (tid == 128) STAMP(19);
        wg_fence();
        {
            const uint64_t db = make_desc(sb + SM_AGG + half * 5120);
#pragma unroll
            for (int ks = 0; ks < 8; ks++) wgmma_n40(acc, da + 2048 + ks * 128, db + (ks >> 2) * 640 + (ks & 3) * 2, 1);
        }
        wg_commit();
        const int t2 = tid & 127, r8 = t2 >> 3, c8 = t2 & 7;
        wg_wait<0>();
        if (tid == 128) STAMP(20);
        const uint32_t ot = sb + SM_EA + (wg - 1) * 6144;
        {
            const int mi = lane >> 3, r = lane & 7;
            const uint32_t a = ot + ((mi >> 1) * 8 + r) * 128 + (((f * 2 + (mi & 1)) ^ r) << 4);
            uint32_t v[10];
#pragma unroll
            for (int i = 0; i < 10; i++) v[i] = pack_bf16(silu_half(0.5f * acc[2 * i]), silu_half(0.5f * acc[2 * i + 1]));
            stsm_x4_trans(a, v[0], v[1], v[2], v[3]);
            stsm_x4_trans(a + 2048, v[4], v[5], v[6], v[7]);
            stsm_x2_trans(a + 4096, v[8], v[9]);
        }
        bar_sync(5 + wg, 128);
        {
            const int lim = min(min(N - cta * NPC, NPC) - half * 40, 40);
            __nv_bfloat16* op = out + (size_t)(cta * NPC + half * 40 + r8) * D + h * 64 + c8 * 8;
            uint4 v[3];
#pragma unroll
            for (int p = 0; p < 3; p++) v[p] = lds128(ot + r8 * 128 + ((c8 ^ (r8 & 7)) << 4) + p * 2048);
#pragma unroll
            for (int p = 0; p < 3; p++)
                if (r8 + 16 * p < lim) stg128(op + 16 * p * D, v[p]);
        }
        if (tid == 128) STAMP(21);
    }
}

__global__ void fb_zero(int n) {
    for (int i = blockIdx.x * blockDim.x + threadIdx.x; i < n; i += gridDim.x * blockDim.x) g_aggf[i] = 0.f;
}
__global__ void fb_edge(const __nv_bfloat16* x, const __nv_bfloat16* e_attr, const int* src, const int* dst,
                        const __nv_bfloat16* w_msg, int E) {
    __shared__ float in[2 * D + DE];
    for (int e = blockIdx.x; e < E; e += gridDim.x) {
        int s = src[e], d = dst[e], c = threadIdx.x;
        __syncthreads();
        in[c] = __bfloat162float(x[(size_t)s * D + c]);
        in[D + c] = __bfloat162float(x[(size_t)d * D + c]);
        if (c < DE) in[2 * D + c] = __bfloat162float(e_attr[(size_t)e * DE + c]);
        __syncthreads();
        float a = 0.f;
        for (int k = 0; k < 2 * D + DE; k++) a = fmaf(in[k], __bfloat162float(w_msg[k * D + c]), a);
        atomicAdd(&g_aggf[(size_t)d * D + c], a / (1.f + __expf(-a)));
    }
}
__global__ void fb_node(const __nv_bfloat16* x, const __nv_bfloat16* w_upd, __nv_bfloat16* out, int N) {
    __shared__ float in[2 * D];
    for (int n = blockIdx.x; n < N; n += gridDim.x) {
        int c = threadIdx.x;
        __syncthreads();
        in[c] = __bfloat162float(x[(size_t)n * D + c]);
        in[D + c] = g_aggf[(size_t)n * D + c];
        __syncthreads();
        float a = 0.f;
        for (int k = 0; k < 2 * D; k++) a = fmaf(in[k], __bfloat162float(w_upd[k * D + c]), a);
        out[(size_t)n * D + c] = __float2bfloat16(a / (1.f + __expf(-a)));
    }
}

}

extern "C" void kernel_launch(void* const* d_in, const int* in_sizes, int n_in, void* d_out, int out_size) {
    const __nv_bfloat16* x = (const __nv_bfloat16*)d_in[0];
    const __nv_bfloat16* e_attr = (const __nv_bfloat16*)d_in[1];
    const int* src = (const int*)d_in[2];
    const int* dst = (const int*)d_in[3];
    const __nv_bfloat16* w_msg = (const __nv_bfloat16*)d_in[4];
    const __nv_bfloat16* w_upd = (const __nv_bfloat16*)d_in[5];
    __nv_bfloat16* out = (__nv_bfloat16*)d_out;
    const int N = in_sizes[0] / D, E = in_sizes[2];

    typedef CUresult (*EncodeFn)(CUtensorMap*, CUtensorMapDataType, cuuint32_t, void*, const cuuint64_t*, const cuuint64_t*,
                                 const cuuint32_t*, const cuuint32_t*, CUtensorMapInterleave, CUtensorMapSwizzle,
                                 CUtensorMapL2promotion, CUtensorMapFloatOOBfill);
    static int mode = -1;
    static void *pP = nullptr, *pSeg = nullptr, *pEp = nullptr;
    static EncodeFn encode = nullptr;
    if (mode < 0) {
        int dev = 0, sms = 0, nb = 0;
        cudaGetDevice(&dev);
        cudaDeviceGetAttribute(&sms, cudaDevAttrMultiProcessorCount, dev);
        cudaError_t e = cudaFuncSetAttribute(mpnn_kernel, cudaFuncAttributeMaxDynamicSharedMemorySize, SM_ALLOC);
        if (e == cudaSuccess) e = cudaOccupancyMaxActiveBlocksPerMultiprocessor(&nb, mpnn_kernel, NT, SM_ALLOC);
        if (e == cudaSuccess) e = cudaGetSymbolAddress(&pP, g_P);
        if (e == cudaSuccess) e = cudaGetSymbolAddress(&pSeg, g_seg);
        if (e == cudaSuccess) e = cudaGetSymbolAddress(&pEp, g_epoch);
        void* fn = nullptr;
        cudaDriverEntryPointQueryResult qr;
        if (e == cudaSuccess) e = cudaGetDriverEntryPoint("cuTensorMapEncodeTiled", &fn, cudaEnableDefault, &qr);
        encode = (EncodeFn)fn;
        mode = (e == cudaSuccess && nb >= 1 && sms >= G && encode != nullptr) ? 1 : 0;
        (void)cudaGetLastError();
    }
    bool fast = mode == 1 && N >= 1 && N <= NMAX && E <= EMAX && (E & 1) == 0;
    CUtensorMap tm[5];
    if (fast) {
        void* base[5] = {(void*)x, (void*)w_msg, (void*)w_upd, pP, (void*)out};
        const cuuint64_t rows[5] = {(cuuint64_t)N, 2 * D + DE, 2 * D, NMAX, (cuuint64_t)N};
        const cuuint32_t boxr[5] = {ROWS, 128, 128, NPC, NPC};
        for (int i = 0; i < 4 && fast; i++) {
            const cuuint64_t dims[2] = {D, rows[i]}, strides[1] = {D * 2};
            const cuuint32_t box[2] = {64, boxr[i]}, es[2] = {1, 1};
            fast = encode(&tm[i], CU_TENSOR_MAP_DATA_TYPE_BFLOAT16, 2, base[i], dims, strides, box, es, CU_TENSOR_MAP_INTERLEAVE_NONE,
                          CU_TENSOR_MAP_SWIZZLE_128B, CU_TENSOR_MAP_L2_PROMOTION_NONE, CU_TENSOR_MAP_FLOAT_OOB_FILL_NONE) == CUDA_SUCCESS;
        }
    }
    if (fast) {
        mpnn_kernel<<<G, NT, SM_ALLOC, cudaStreamPerThread>>>(e_attr, src, dst, w_msg, w_upd, out, (__nv_bfloat16*)pP, (uint32_t*)pSeg,
                                                              (uint32_t*)pEp, N, E, tm[0], tm[1], tm[2], tm[3]);
    } else {
        fb_zero<<<256, 256, 0, cudaStreamPerThread>>>(N * D);
        fb_edge<<<2048, D, 0, cudaStreamPerThread>>>(x, e_attr, src, dst, w_msg, E);
        fb_node<<<2048, D, 0, cudaStreamPerThread>>>(x, w_upd, out, N);
    }
}
```

```cpp
#include <cuda.h>
#include <cuda_runtime.h>
#include <cuda_bf16.h>
#include <stdint.h>

namespace {

constexpr int D = 128;
constexpr int DE = 16;
constexpr int G = 132;
constexpr int NPC = 76;
constexpr int ROWS = 80;
constexpr int EPC = 1216;
constexpr int NT = 640;
constexpr int NMAX = G * NPC;
constexpr int EMAX = G * EPC;
constexpr int SEGCAP = 32;

constexpr int NTILE = 120;
constexpr int SM_XS = 0;
constexpr int SM_W = 20480;
constexpr int SM_AGG = SM_W + 65536;
constexpr int EAROWS = 1536;
constexpr int SM_EA = SM_AGG + 20480;
constexpr int SM_LIST = SM_EA + EAROWS * 32;
constexpr int TRASH = (NTILE + 4) * 16;
constexpr int SM_EL = SM_LIST + 8000;
constexpr int SM_EG = SM_EL + 8000;
constexpr int SM_W3F = SM_EG + 13312;
constexpr int SM_W3G = SM_W3F + 4096;
constexpr int SM_MISC = SM_W3G + 4096;
constexpr int SM_STG = SM_AGG;
constexpr int SM_TOTAL = SM_MISC + 3328;
constexpr int SM_ALLOC = SM_TOTAL + 1024;
constexpr int MI_SEG = 0;
constexpr int MI_SLOW = 544;
constexpr int MI_ECNT = 548;
constexpr int MI_TICKET = 552;
constexpr int MI_KEY = 560;
constexpr int MI_MB = 3264;
constexpr int MI_TAG = 1072;
constexpr int MI_PERM = 1088;
constexpr int MI_SKEY = 1408;
constexpr int MI_NREC = 1728;
constexpr int MI_ID = 2752;

constexpr uint32_t W_EMPTY = 0xFFFFFFFFu;
constexpr uint32_t T_EMPTY = 0x7FFFFFFFu;
constexpr uint32_t T_OVF = 0x7FFFBFFFu;
constexpr int GBLIND = 4;
constexpr int SPIN_LIMIT = 1 << 20;

__device__ __align__(256) __nv_bfloat16 g_P[(NMAX + G) * D];
__device__ __align__(256) uint32_t g_seg[G * G * SEGCAP];
__device__ __align__(256) unsigned long long g_epoch[32];
__device__ float g_aggf[4 * 1024 * 1024];
#define STAMP(i) do { } while (0)

__device__ __forceinline__ uint32_t smem_u32(const void* p) { return (uint32_t)__cvta_generic_to_shared(p); }
__device__ __forceinline__ void fence_async() { asm volatile("fence.proxy.async.shared::cta;" ::: "memory"); }
__device__ __forceinline__ void bar_sync(int id, int n) { asm volatile("bar.sync %0, %1;" ::"r"(id), "r"(n) : "memory"); }
__device__ __forceinline__ void bar_arrive(int id, int n) { asm volatile("bar.arrive %0, %1;" ::"r"(id), "r"(n) : "memory"); }
__device__ __forceinline__ uint32_t lds32(uint32_t a) { uint32_t v; asm volatile("ld.shared.u32 %0, [%1];" : "=r"(v) : "r"(a) : "memory"); return v; }
__device__ __forceinline__ uint2 lds64(uint32_t a) { uint2 v; asm volatile("ld.shared.v2.u32 {%0,%1}, [%2];" : "=r"(v.x), "=r"(v.y) : "r"(a) : "memory"); return v; }
__device__ __forceinline__ uint4 lds128(uint32_t a) { uint4 v; asm volatile("ld.shared.v4.u32 {%0,%1,%2,%3}, [%4];" : "=r"(v.x), "=r"(v.y), "=r"(v.z), "=r"(v.w) : "r"(a) : "memory"); return v; }
__device__ __forceinline__ void sts32(uint32_t a, uint32_t v) { asm volatile("st.shared.u32 [%0], %1;" ::"r"(a), "r"(v) : "memory"); }
__device__ __forceinline__ void sts128(uint32_t a, uint4 v) { asm volatile("st.shared.v4.u32 [%0], {%1,%2,%3,%4};" ::"r"(a), "r"(v.x), "r"(v.y), "r"(v.z), "r"(v.w) : "memory"); }
__device__ __forceinline__ void sts32_lt(uint32_t a, uint32_t v, uint32_t x, uint32_t lim) {
    asm volatile("{\n.reg .pred p;\nsetp.lt.u32 p, %2, %3;\n@p st.shared.u32 [%0], %1;\n}" ::"r"(a), "r"(v), "r"(x), "r"(lim) : "memory");
}
__device__ __forceinline__ void sts64_lt(uint32_t a, uint32_t v, uint32_t w, uint32_t x, uint32_t lim) {
    asm volatile("{\n.reg .pred p;\nsetp.lt.u32 p, %3, %4;\n@p st.shared.v2.u32 [%0], {%1, %2};\n}" ::"r"(a), "r"(v), "r"(w), "r"(x), "r"(lim) : "memory");
}
__device__ __forceinline__ void cp_async16_lt(uint32_t dst, const void* src, int x, int lim) {
    asm volatile("{\n.reg .pred p;\nsetp.lt.s32 p, %2, %3;\n@p cp.async.cg.shared.global [%0], [%1], 16;\n}" ::"r"(dst), "l"(src), "r"(x), "r"(lim) : "memory");
}
__device__ __forceinline__ uint32_t atoms_add_lt(uint32_t a, int d, uint32_t x, uint32_t lim) {
    uint32_t v = 0;
    asm volatile("{\n.reg .pred p;\nsetp.lt.u32 p, %3, %4;\n@p atom.shared.add.u32 %0, [%1], %2;\n}" : "+r"(v) : "r"(a), "r"(d), "r"(x), "r"(lim) : "memory");
    return v;
}
__device__ __forceinline__ uint32_t atoms_add(uint32_t a, int d) { uint32_t v; asm volatile("atom.shared.add.u32 %0, [%1], %2;" : "=r"(v) : "r"(a), "r"(d) : "memory"); return v; }
__device__ __forceinline__ uint4 ldg128(const void* p) { uint4 v; asm volatile("ld.global.v4.u32 {%0,%1,%2,%3}, [%4];" : "=r"(v.x), "=r"(v.y), "=r"(v.z), "=r"(v.w) : "l"(p) : "memory"); return v; }
__device__ __forceinline__ uint2 ldg64(const void* p) { uint2 v; asm volatile("ld.global.v2.u32 {%0,%1}, [%2];" : "=r"(v.x), "=r"(v.y) : "l"(p) : "memory"); return v; }
__device__ __forceinline__ void sts64(uint32_t a, uint32_t x, uint32_t y) { asm volatile("st.shared.v2.u32 [%0], {%1,%2};" ::"r"(a), "r"(x), "r"(y) : "memory"); }
__device__ __forceinline__ void stg128(void* p, uint4 v) { asm volatile("st.global.v4.u32 [%0], {%1,%2,%3,%4};" ::"l"(p), "r"(v.x), "r"(v.y), "r"(v.z), "r"(v.w) : "memory"); }
__device__ __forceinline__ uint32_t pack_bf16(float lo, float hi) {
    uint32_t r; asm("cvt.rn.bf16x2.f32 %0, %1, %2;" : "=r"(r) : "f"(hi), "f"(lo)); return r;
}
__device__ __forceinline__ float tanh_fast(float x) { float r; asm("tanh.approx.f32 %0, %1;" : "=f"(r) : "f"(x)); return r; }
__device__ __forceinline__ float silu_half(float h) { return fmaf(h, tanh_fast(h), h); }
__device__ __forceinline__ uint32_t movm(uint32_t a) { uint32_t d; asm volatile("movmatrix.sync.aligned.m8n8.trans.b16 %0, %1;" : "=r"(d) : "r"(a)); return d; }
__device__ __forceinline__ uint32_t shl_clamp(uint32_t v, uint32_t s) { uint32_t d; asm("shl.b32 %0, %1, %2;" : "=r"(d) : "r"(v), "r"(s)); return d; }
__device__ __forceinline__ void mma16(float (&d)[4], uint32_t a0, uint32_t a1, uint32_t a2, uint32_t a3, uint32_t b0, uint32_t b1) {
    asm("mma.sync.aligned.m16n8k16.row.col.f32.bf16.bf16.f32 {%0,%1,%2,%3}, {%4,%5,%6,%7}, {%8,%9}, {%0,%1,%2,%3};"
        : "+f"(d[0]), "+f"(d[1]), "+f"(d[2]), "+f"(d[3]) : "r"(a0), "r"(a1), "r"(a2), "r"(a3), "r"(b0), "r"(b1));
}
__device__ __forceinline__ void mma16_c(float (&d)[4], uint32_t a0, uint32_t a1, uint32_t a2, uint32_t a3, uint32_t b0, uint32_t b1, const float (&c)[4]) {
    asm("mma.sync.aligned.m16n8k16.row.col.f32.bf16.bf16.f32 {%0,%1,%2,%3}, {%4,%5,%6,%7}, {%8,%9}, {%10,%11,%12,%13};"
        : "=f"(d[0]), "=f"(d[1]), "=f"(d[2]), "=f"(d[3]) : "r"(a0), "r"(a1), "r"(a2), "r"(a3), "r"(b0), "r"(b1),
          "f"(c[0]), "f"(c[1]), "f"(c[2]), "f"(c[3]));
}
__device__ __forceinline__ void stsm_x4_trans(uint32_t addr, uint32_t r0, uint32_t r1, uint32_t r2, uint32_t r3) {
    asm volatile("stmatrix.sync.aligned.m8n8.x4.trans.shared.b16 [%0], {%1,%2,%3,%4};" ::"r"(addr), "r"(r0), "r"(r1), "r"(r2), "r"(r3) : "memory");
}

__device__ __forceinline__ uint64_t make_desc(uint32_t addr) {
    return (uint64_t)((addr & 0x3FFFF) >> 4) | ((uint64_t)64 << 16) | ((uint64_t)64 << 32) | ((uint64_t)1 << 62);
}
__device__ __forceinline__ void wg_fence() { asm volatile("wgmma.fence.sync.aligned;" ::: "memory"); }
__device__ __forceinline__ void wg_commit() { asm volatile("wgmma.commit_group.sync.aligned;" ::: "memory"); }
template <int N> __device__ __forceinline__ void wg_wait() { asm volatile("wgmma.wait_group.sync.aligned %0;" ::"n"(N) : "memory"); }
__device__ __forceinline__ void wgmma_n80(float (&d)[40], uint64_t da, uint64_t db, int scale_d) {
    asm volatile(
        "{\n.reg .pred p;\nsetp.ne.b32 p, %42, 0;\n"
        "wgmma.mma_async.sync.aligned.m64n80k16.f32.bf16.bf16 "
        "{%0,%1,%2,%3,%4,%5,%6,%7,%8,%9,%10,%11,%12,%13,%14,%15,%16,%17,%18,%19,"
        "%20,%21,%22,%23,%24,%25,%26,%27,%28,%29,%30,%31,%32,%33,%34,%35,%36,%37,%38,%39}, "
        "%40, %41, p, 1, 1, 1, 0;\n}\n"
        : "+f"(d[0]), "+f"(d[1]), "+f"(d[2]), "+f"(d[3]), "+f"(d[4]), "+f"(d[5]), "+f"(d[6]), "+f"(d[7]), "+f"(d[8]), "+f"(d[9]),
          "+f"(d[10]), "+f"(d[11]), "+f"(d[12]), "+f"(d[13]), "+f"(d[14]), "+f"(d[15]), "+f"(d[16]), "+f"(d[17]), "+f"(d[18]), "+f"(d[19]),
          "+f"(d[20]), "+f"(d[21]), "+f"(d[22]), "+f"(d[23]), "+f"(d[24]), "+f"(d[25]), "+f"(d[26]), "+f"(d[27]), "+f"(d[28]), "+f"(d[29]),
          "+f"(d[30]), "+f"(d[31]), "+f"(d[32]), "+f"(d[33]), "+f"(d[34]), "+f"(d[35]), "+f"(d[36]), "+f"(d[37]), "+f"(d[38]), "+f"(d[39])
        : "l"(da), "l"(db), "r"(scale_d));
}

__device__ __forceinline__ void wgmma_n40(float (&d)[20], uint64_t da, uint64_t db, int scale_d) {
    asm volatile(
        "{\n.reg .pred p;\nsetp.ne.b32 p, %22, 0;\n"
        "wgmma.mma_async.sync.aligned.m64n40k16.f32.bf16.bf16 "
        "{%0,%1,%2,%3,%4,%5,%6,%7,%8,%9,%10,%11,%12,%13,%14,%15,%16,%17,%18,%19}, "
        "%20, %21, p, 1, 1, 1, 0;\n}\n"
        : "+f"(d[0]), "+f"(d[1]), "+f"(d[2]), "+f"(d[3]), "+f"(d[4]), "+f"(d[5]), "+f"(d[6]), "+f"(d[7]), "+f"(d[8]), "+f"(d[9]),
          "+f"(d[10]), "+f"(d[11]), "+f"(d[12]), "+f"(d[13]), "+f"(d[14]), "+f"(d[15]), "+f"(d[16]), "+f"(d[17]), "+f"(d[18]), "+f"(d[19])
        : "l"(da), "l"(db), "r"(scale_d));
}
__device__ __forceinline__ void stsm_x2_trans(uint32_t addr, uint32_t r0, uint32_t r1) {
    asm volatile("stmatrix.sync.aligned.m8n8.x2.trans.shared.b16 [%0], {%1,%2};" ::"r"(addr), "r"(r0), "r"(r1) : "memory");
}
__device__ __forceinline__ uint4 ldg128_rlx(const void* p) { uint4 v; asm volatile("ld.relaxed.gpu.global.v4.u32 {%0,%1,%2,%3}, [%4];" : "=r"(v.x), "=r"(v.y), "=r"(v.z), "=r"(v.w) : "l"(p) : "memory"); return v; }
__device__ __forceinline__ void stg128_rlx(void* p, uint4 v) { asm volatile("st.relaxed.gpu.global.v4.u32 [%0], {%1,%2,%3,%4};" ::"l"(p), "r"(v.x), "r"(v.y), "r"(v.z), "r"(v.w) : "memory"); }

__device__ __forceinline__ unsigned long long ldg64_rlx(const void* p) { unsigned long long v; asm volatile("ld.relaxed.gpu.global.u64 %0, [%1];" : "=l"(v) : "l"(p) : "memory"); return v; }
__device__ __forceinline__ void hint_arrive(unsigned long long* p) { asm volatile("red.relaxed.gpu.global.add.u64 [%0], 1;" ::"l"(p) : "memory"); }
__device__ __forceinline__ void hint_wait(const unsigned long long* p, unsigned long long target) {
#pragma unroll 1
    for (int it = 0; it < SPIN_LIMIT; it++)
        if (ldg64_rlx(p) >= target) break;
}

__host__ __device__ constexpr int boundary(int k) { return k == 0 ? 8 : 24 + 21 * k; }
__device__ __forceinline__ uint32_t tile_addr(uint32_t base, int row, int c) {
    return base + (c >> 3) * 10240 + row * 128 + (((c & 7) ^ (row & 7)) << 4);
}

__device__ __forceinline__ uint32_t split_cap(uint32_t sm) {
    const int d0 = lds32(sm + MI_SKEY) >> 7, d4 = lds32(sm + MI_SKEY + 16) >> 7, d72 = lds32(sm + MI_SKEY + 288) >> 7;
    return max(d4, d0 - ((d72 + 1) & ~1));
}

struct Tile { uint4 p0, p1; };
struct Consts { uint4 w3[2]; uint4 id; uint32_t par, q8; const unsigned char* pb; };

__device__ __forceinline__ void fetch(Tile& st, uint32_t la, const Consts& k) {
    uint2 e = lds64(la);
    st.p0 = ldg128_rlx(k.pb + (size_t)e.x * 256);
    st.p1 = ldg128_rlx(k.pb + (size_t)e.y * 256);
}
__device__ __forceinline__ bool stale(const Tile& a, const Tile& b, const Consts& k) {
    uint32_t t, u;
    asm("lop3.b32 %0, %1, %2, %3, 0x7E;" : "=r"(t) : "r"(a.p0.x), "r"(a.p1.x), "r"(k.par));
    asm("lop3.b32 %0, %1, %2, %3, 0x7E;" : "=r"(u) : "r"(b.p0.x), "r"(b.p1.x), "r"(k.par));
    asm("lop3.b32 %0, %1, %2, 1, 0xA8;" : "=r"(t) : "r"(t), "r"(u));
    return __any_sync(0xffffffffu, t != 0);
}
__device__ __forceinline__ void validate(Tile& a, Tile& b, uint32_t la, const Consts& k) {
    if (__builtin_expect(stale(a, b, k), 0)) {
#pragma unroll 1
        for (int it = 0; it < SPIN_LIMIT; it++) {
            fetch(a, la, k);
            fetch(b, la + 64, k);
            if (!stale(a, b, k)) break;
        }
    }
}
__device__ __forceinline__ void tile_mma(float (&acc)[2][4], const Tile& st, uint2 eo, const float (&qi)[2][4], const Consts& k) {
    const uint2 ea0 = lds64(eo.x | k.q8), ea1 = lds64(eo.y | k.q8);
    float c[2][2][4];
#pragma unroll
    for (int u = 0; u < 2; u++) {
        mma16_c(c[u][0], k.id.x, k.id.y, k.id.z, k.id.w, u ? st.p0.z : st.p0.x, u ? st.p0.w : st.p0.y, qi[u]);
        mma16_c(c[u][1], k.id.x, k.id.y, k.id.z, k.id.w, u ? st.p1.z : st.p1.x, u ? st.p1.w : st.p1.y, qi[u]);
    }
#pragma unroll
    for (int u = 0; u < 2; u++) {
        mma16(c[u][0], k.w3[u].x, k.w3[u].y, k.w3[u].z, k.w3[u].w, ea0.x, ea0.y);
        mma16(c[u][1], k.w3[u].x, k.w3[u].y, k.w3[u].z, k.w3[u].w, ea1.x, ea1.y);
    }
#pragma unroll
    for (int u = 0; u < 2; u++)
#pragma unroll
        for (int n = 0; n < 2; n++)
#pragma unroll
            for (int i = 0; i < 4; i++) acc[u][i] += silu_half(c[u][n][i]);
}
__device__ __forceinline__ void load_q(float (&qi)[2][4], uint32_t sb, int ra, int rb, int f, int g) {
    const uint4 a = lds128(tile_addr(sb + SM_AGG, ra, 4 * f + (g >> 1))), b = lds128(tile_addr(sb + SM_AGG, rb, 4 * f + (g >> 1)));
    const uint32_t sel = (g & 1) ? 0x3244u : 0x1044u;
    qi[0][0] = 0.5f * __uint_as_float(__byte_perm(a.x, 0, sel)); qi[0][1] = 0.5f * __uint_as_float(__byte_perm(b.x, 0, sel));
    qi[0][2] = 0.5f * __uint_as_float(__byte_perm(a.y, 0, sel)); qi[0][3] = 0.5f * __uint_as_float(__byte_perm(b.y, 0, sel));
    qi[1][0] = 0.5f * __uint_as_float(__byte_perm(a.z, 0, sel)); qi[1][1] = 0.5f * __uint_as_float(__byte_perm(b.z, 0, sel));
    qi[1][2] = 0.5f * __uint_as_float(__byte_perm(a.w, 0, sel)); qi[1][3] = 0.5f * __uint_as_float(__byte_perm(b.w, 0, sel));
}
__device__ __forceinline__ void flush_agg(uint32_t addr, const float (&acc)[2][4]) {
    uint4 v;
    v.x = movm(pack_bf16(acc[0][0], acc[0][1]));
    v.y = movm(pack_bf16(acc[0][2], acc[0][3]));
    v.z = movm(pack_bf16(acc[1][0], acc[1][1]));
    v.w = movm(pack_bf16(acc[1][2], acc[1][3]));
    sts128(addr, v);
}

__device__ __forceinline__ void tma_load(uint32_t dst, const CUtensorMap* tm, int c0, int c1, uint32_t mbar) {
    asm volatile("cp.async.bulk.tensor.2d.shared::cluster.global.mbarrier::complete_tx::bytes [%0], [%1, {%2, %3}], [%4];"
                 ::"r"(dst), "l"(tm), "r"(c0), "r"(c1), "r"(mbar) : "memory");
}
__device__ __forceinline__ void tma_store(const CUtensorMap* tm, int c0, int c1, uint32_t src) {
    asm volatile("cp.async.bulk.tensor.2d.global.shared::cta.bulk_group [%0, {%1, %2}], [%3];" ::"l"(tm), "r"(c0), "r"(c1), "r"(src) : "memory");
    asm volatile("cp.async.bulk.commit_group;" ::: "memory");
}
__device__ __forceinline__ void tma_store_wait() { asm volatile("cp.async.bulk.wait_group.read 0;" ::: "memory"); }
__device__ __forceinline__ void mbar_wait0(uint32_t a) {
    for (int it = 0; it < SPIN_LIMIT; it++) {
        uint32_t ok;
        asm volatile("{\n.reg .pred p;\nmbarrier.try_wait.parity.shared::cta.b64 p, [%1], 0;\nselp.u32 %0, 1, 0, p;\n}" : "=r"(ok) : "r"(a) : "memory");
        if (ok) break;
    }
}

__device__ __noinline__ void slow_path(uint32_t sb, const __nv_bfloat16* e_attr, const int* src, const int* dst, int E, Consts k) {
    const int tid = threadIdx.x, lane = tid & 31, wg = tid >> 7, f = (tid >> 5) & 3, g = lane >> 2, q = lane & 3, cta = blockIdx.x;
    const uint32_t s_deg = sb + SM_MISC + MI_KEY;
    float acc[2][2][4];
    for (int i = 0; i < 16; i++) (&acc[0][0][0])[i] = 0.f;
    int scan = 0, state = 0, row = 0;
    bool more = true;
    while (more) {
        more = false;
        __syncthreads();
        if (tid < ROWS) sts32(s_deg + tid * 4, 0);
        for (int i = tid; i < EAROWS * 2; i += NT) sts128(sb + SM_EA + i * 16, make_uint4(0, 0, 0, 0));
        for (int i = tid; i < (NTILE + 4) * 16; i += NT) sts32(sb + SM_LIST + i * 4, NMAX + cta);
        __syncthreads();
        while (true) {
            const int e = scan + tid;
            if (state == 0) {
                state = 2;
                if (e < E) {
                    int dn = dst[e];
                    if (dn / NPC == cta) { state = 1; row = dn - cta * NPC; }
                }
            }
            if (state == 1) {
                uint32_t rank = atoms_add(s_deg + row * 4, 1);
                if (rank < 18) {
                    uint32_t pos = ((row >> 3) * 9 + (rank >> 1)) * 16 + (row & 7) * 2 + (rank & 1);
                    sts32(sb + SM_LIST + pos * 4, (uint32_t)src[e]);
                    sts128(sb + SM_EA + pos * 32, ldg128(e_attr + (size_t)e * DE));
                    sts128(sb + SM_EA + pos * 32 + 16, ldg128(e_attr + (size_t)e * DE + 8));
                    state = 2;
                }
            }
            if (__syncthreads_or(state == 1)) { more = true; break; }
            scan += NT;
            state = 0;
            if (scan >= E) break;
        }
#pragma unroll
        for (int b = 0; b < 2; b++) {
            const int grp = 2 * wg + b;
            const int mx = min((int)__reduce_max_sync(0xffffffffu, lds32(s_deg + (grp * 8 + g) * 4)), 18);
            float qi[2][4];
            load_q(qi, sb, grp * 8 + 2 * q, grp * 8 + 2 * q + 1, f, g);
            for (int t = 0; t * 2 < mx; t++) {
                const int tile = grp * 9 + t;
                Tile st, s2;
                const uint32_t la = sb + SM_LIST + tile * 64 + g * 8;
                fetch(st, la, k);
                fetch(s2, la + 64, k);
                validate(st, s2, la, k);
                tile_mma(acc[b], st, make_uint2(sb + SM_EA + tile * 512 + g * 64, sb + SM_EA + tile * 512 + g * 64 + 32), qi, k);
            }
        }
    }
    __syncwarp();
    flush_agg(tile_addr(sb + SM_AGG, wg * 16 + g, 4 * f + q), acc[0]);
    flush_agg(tile_addr(sb + SM_AGG, wg * 16 + 8 + g, 4 * f + q), acc[1]);
}

__global__ void __launch_bounds__(NT, 1)
mpnn_kernel(const __nv_bfloat16* __restrict__ e_attr, const int* __restrict__ src, const int* __restrict__ dst,
            const __nv_bfloat16* __restrict__ w_msg, const __nv_bfloat16* __restrict__ w_upd,
            __nv_bfloat16* __restrict__ out, __nv_bfloat16* __restrict__ gP, uint32_t* __restrict__ gseg,
            unsigned long long* __restrict__ gepoch, int N, int E,
            const __grid_constant__ CUtensorMap tm_x, const __grid_constant__ CUtensorMap tm_wm,
            const __grid_constant__ CUtensorMap tm_wu, const __grid_constant__ CUtensorMap tm_p) {
    extern __shared__ unsigned char smem_raw[];
    const uint32_t sb = (smem_u32(smem_raw) + 1023u) & ~1023u;
    const int tid = threadIdx.x, warp = tid >> 5, lane = tid & 31;
    const int wg = warp >> 2, f = warp & 3, g = lane >> 2, q = lane & 3;
    const int cta = blockIdx.x;
    const int wgu = (int)__reduce_max_sync(0xffffffffu, (uint32_t)wg);
    const uint32_t sm = sb + SM_MISC;
    if (tid == 0) STAMP(0);

    uint2 d2 = make_uint2(~0u, 0), s2;
    {
        const int e0 = ((tid >> 4) * G + cta) * 32 + (tid & 15) * 2;
        if (tid < EPC / 2 && e0 < E) {
            d2 = ldg64(dst + e0);
            s2 = ldg64(src + e0);
        }
    }
    unsigned long long cnt0 = 0;
    if (tid == 608) cnt0 = ldg64_rlx(gepoch);
    sts128(sb + SM_STG + tid * 16, make_uint4(W_EMPTY, W_EMPTY, W_EMPTY, W_EMPTY));
    if (tid < 416) sts128(sb + SM_STG + 10240 + tid * 16, make_uint4(W_EMPTY, W_EMPTY, W_EMPTY, W_EMPTY));
    else if (tid < 636) sts32(sm + (tid - 416) * 4, tid >= 556 ? 127 - (tid - 556) : tid == 553);
    if (warp == 19) {
        if (lane == 31) {
            asm volatile("mbarrier.init.shared::cta.b64 [%0], 1;" ::"r"(sm + MI_MB) : "memory");
            asm volatile("mbarrier.init.shared::cta.b64 [%0], 1;" ::"r"(sm + MI_MB + 8) : "memory");
            asm volatile("mbarrier.init.shared::cta.b64 [%0], 96;" ::"r"(sm + MI_MB + 16) : "memory");
            asm volatile("mbarrier.init.shared::cta.b64 [%0], 96;" ::"r"(sm + MI_MB + 24) : "memory");
            asm volatile("mbarrier.init.shared::cta.b64 [%0], 20;" ::"r"(sm + MI_MB + 32) : "memory");
            sts64(sm + MI_NREC + 127 * 8, 0x40000000u, 0u);
        }
        __syncwarp();
        bar_arrive(3, 640);
        if (lane == 31) {
            fence_async();
            asm volatile("mbarrier.arrive.expect_tx.shared::cta.b64 _, [%0], %1;" ::"r"(sm + MI_MB), "r"(20480 + 65536 + 4096) : "memory");
            asm volatile("mbarrier.arrive.expect_tx.shared::cta.b64 _, [%0], %1;" ::"r"(sm + MI_MB + 8), "r"(65536) : "memory");
#pragma unroll
            for (int b = 0; b < 4; b++) tma_load(sb + SM_W + b * 16384, &tm_wm, (b & 1) * 64, (b >> 1) * 128, sm + MI_MB);
            asm volatile("cp.async.bulk.shared::cluster.global.mbarrier::complete_tx::bytes [%0], [%1], 4096, [%2];"
                         ::"r"(sb + SM_W3F), "l"(w_msg + 2 * D * D), "r"(sm + MI_MB) : "memory");
            tma_load(sb + SM_XS, &tm_x, 0, cta * NPC, sm + MI_MB);
            tma_load(sb + SM_XS + 10240, &tm_x, 64, cta * NPC, sm + MI_MB);
            asm volatile("prefetch.tensormap [%0];" ::"l"(&tm_p) : "memory");
            asm volatile("prefetch.tensormap [%0];" ::"l"(&tm_wu) : "memory");
        }
        __syncwarp();
    } else {
        bar_sync(3, 640);
    }
    if (tid == 0) STAMP(23);
    if (tid >= 636)
        asm volatile("prefetch.global.L2 [%0];" ::"l"(reinterpret_cast<const unsigned char*>(w_upd) + min(cta * 4 + (tid - 636), 511) * 128));
    if (d2.x != ~0u) {
        const uint32_t dc0 = d2.x / NPC, dc1 = d2.y / NPC;
        const uint32_t r0 = atoms_add(sm + MI_SEG + dc0 * 4, 1), r1 = atoms_add(sm + MI_SEG + dc1 * 4, 1);
        const uint32_t w0 = s2.x | (((tid << 8) + d2.x - dc0 * NPC) << 14), w1 = s2.y | (((tid << 8) + 128 + d2.y - dc1 * NPC) << 14);
        sts32_lt(sb + SM_STG + dc0 * 128 + (r0 & 7) * 16 + (r0 >> 3) * 4, w0, r0, SEGCAP);
        sts32_lt(sb + SM_STG + dc1 * 128 + (r1 & 7) * 16 + (r1 >> 3) * 4, w1, r1, SEGCAP);
    }
    if (tid == 608) {
        cnt0 = cnt0 / G + 1;
        sts32(sm + MI_TAG, (uint32_t)cnt0);
    }
    if (tid == 0) STAMP(24);
    __syncthreads();
    const uint32_t tag = lds32(sm + MI_TAG);
    const uint32_t parw = tag << 31;
    {
        uint4 v[2];
        uint32_t cn[2];
#pragma unroll
        for (int i = 0; i < 2; i++) {
            v[i] = lds128(sb + SM_STG + tid * 16 + i * 10240);
            cn[i] = lds32(sm + MI_SEG + min((tid >> 3) + i * 80, 135) * 4);
        }
#pragma unroll
        for (int i = 0; i < 2; i++) {
            uint32_t tl = T_EMPTY;
            if (cn[i] > 24) {
                const uint32_t w = v[i].w;
                if (w != W_EMPTY) tl = (((w >> 21) * ROWS + ((w >> 14) & 127u)) << 14) | (w & 16383u);
                if (cn[i] > SEGCAP) tl = T_OVF;
            }
            v[i].w = tl | parw;
            if (i == 0 || tid < 416) stg128_rlx(gseg + (size_t)cta * (G * SEGCAP) + tid * 4 + i * 2560, v[i]);
        }
    }
    const uint32_t* bp = gseg + ((size_t)(tid >> 3) * G + cta) * SEGCAP + (tid & 7) * 4;
    uint4 v1 = make_uint4(W_EMPTY, W_EMPTY, W_EMPTY, T_EMPTY | parw), v0 = v1;
    auto prefill2 = [&]() {
        const uint32_t pr = NMAX + cta;
        if (tid < 496) sts128(sb + SM_LIST + tid * 16, make_uint4(pr, pr, pr, pr));
        if (tid >= 144) sts128(sb + SM_EL + (tid - 144) * 16, make_uint4(sb + SM_EA, sb + SM_EA, sb + SM_EA, sb + SM_EA));
        else if (tid >= 142) sts128(sb + SM_EA + (tid - 142) * 16, make_uint4(0, 0, 0, 0));
        else if (tid < 32) {
            uint32_t idf = shl_clamp(0x3F00u, (uint32_t)((g - 2 * q) << 4));
            sts128(sm + MI_ID + lane * 16, make_uint4(idf, 0, 0, idf));
        }
    };
    if (wg < 4) {
        bar_arrive(2, 640);
        prefill2();
        mbar_wait0(sm + MI_MB);
        if (tid == 0) STAMP(1);
        if (tid == 255) {
            int eb = cta * EPC, ne = min(EPC, E - eb);
            if (ne > 0) asm volatile("cp.async.bulk.prefetch.L2.global [%0], %1;" ::"l"(e_attr + (size_t)eb * DE), "r"(ne * 32) : "memory");
        }
        float gacc[40];
        const uint64_t da = make_desc(sb + SM_W + wgu * 16384), db = make_desc(sb + SM_XS);
        wg_fence();
#pragma unroll
        for (int ks = 0; ks < 8; ks++) wgmma_n80(gacc, da + ks * 128, db + (ks >> 2) * 640 + (ks & 3) * 2, ks);
        wg_commit();
        bar_sync(4, 640);
        if (tid == 0) STAMP(22);
        v0 = ldg128_rlx(bp);
        v1 = ldg128_rlx(bp + (size_t)68 * G * SEGCAP);
        const uint32_t so = (wg < 2 ? sb + SM_W + wg * 16384 : sb + SM_AGG + (wg - 2) * 10240) +
                            (((lane >> 4) & 1) * 8 + (lane & 7)) * 128 + (((f * 2 + ((lane >> 3) & 1)) ^ (lane & 7)) << 4);
        const bool pm = wg < 2 && g == 0;
        const uint32_t keep = pm ? 0xFFFEFFFEu : 0xFFFFFFFFu, setb = pm ? (tag & 1u) * 0x10001u : 0u;
        wg_wait<0>();
        if (tid == 0) STAMP(2);
        if (wg < 2) bar_sync(7 + wg, 128);
#pragma unroll
        for (int j = 0; j < 5; j++)
            stsm_x4_trans(so + j * 2048,
                          (pack_bf16(gacc[8 * j], gacc[8 * j + 1]) & keep) | setb, (pack_bf16(gacc[8 * j + 2], gacc[8 * j + 3]) & keep) | setb,
                          (pack_bf16(gacc[8 * j + 4], gacc[8 * j + 5]) & keep) | setb, (pack_bf16(gacc[8 * j + 6], gacc[8 * j + 7]) & keep) | setb);
        if (wg < 2) fence_async();
        bar_arrive(5, 544);
    } else {
        if (warp < 19) bar_arrive(2, 640);
        prefill2();
        if (tid >= 624)
            stg128_rlx(gP + (size_t)(NMAX + cta) * D + (tid - 624) * 8, make_uint4(0xFF00FF00u | (tag & 1u), 0xFF00FF00u, 0xFF00FF00u, 0xFF00FF00u));
        if (warp == 19) {
            bar_sync(2, 640);
            if (lane == 0) { STAMP(4); hint_arrive(gepoch); hint_wait(gepoch, cnt0 * G); STAMP(7); }
            __syncwarp();
        } else {
            mbar_wait0(sm + MI_MB);
#pragma unroll 1
            for (int ff = f; ff < 4; ff += 3) {
                const uint32_t wa = sb + SM_W3F + (4 * q * D + 32 * ff + (g >> 1) * 8 + (g & 1)) * 2;
                uint32_t w[8];
#pragma unroll
                for (int i = 0; i < 8; i++) {
                    const int u = i >> 2, r = i & 3, o = 4 * u + 2 * (r & 1) + 2 * (r >> 1) * D;
                    unsigned short lo, hi;
                    asm volatile("ld.shared.u16 %0, [%1];" : "=h"(lo) : "r"(wa + o * 2));
                    asm volatile("ld.shared.u16 %0, [%1];" : "=h"(hi) : "r"(wa + (o + D) * 2));
                    asm("mul.bf16x2 %0, %1, %2;" : "=r"(w[i]) : "r"((uint32_t)lo | ((uint32_t)hi << 16)), "r"(0x3F003F00u));
                }
                sts128(sb + SM_W3G + ff * 1024 + lane * 16, make_uint4(w[0], w[1], w[2], w[3]));
                sts128(sb + SM_W3G + ff * 1024 + 512 + lane * 16, make_uint4(w[4], w[5], w[6], w[7]));
            }
        }
        bar_sync(4, 640);
        if (warp == 16) v0 = ldg128_rlx(bp);
    }
    if (warp >= 17) {
        if (warp == 17) {
            bar_sync(5, 544);
            if (lane == 0) {
                tma_store(&tm_p, 0, cta * NPC, sb + SM_W);
                tma_store(&tm_p, 64, cta * NPC, sb + SM_W + 16384);
                tma_load(sb + SM_W + 32768, &tm_wu, 0, 128, sm + MI_MB + 8);
                tma_load(sb + SM_W + 49152, &tm_wu, 64, 128, sm + MI_MB + 8);
                STAMP(3);
            }
            __syncwarp();
        }
        bar_sync(6, 640);
        const int n = min((int)lds32(sm + MI_ECNT), EAROWS);
        const unsigned char* geb = reinterpret_cast<const unsigned char*>(e_attr) + (lane & 1) * 16;
        const int n0 = lds32(sm + MI_SLOW) == 0 ? n : 0;
        const int r0 = 1 + (lane >> 1) + (warp - 17) * 32;
#pragma unroll
        for (int it = 0; it < GBLIND; it++)
#pragma unroll
            for (int j = 0; j < 2; j++) {
                const int r = r0 + it * 96 + j * 16;
                cp_async16_lt(sb + SM_EA + r * 32 + (lane & 1) * 16, geb + lds32(sb + SM_EG + r * 8), r, n0);
            }
        constexpr int GR = 28 - 2 * GBLIND;
        uint2 rc[GR];
#pragma unroll
        for (int j = 0; j < GR; j++) rc[j] = lds64(sb + SM_EG + (r0 + (GBLIND + (j >> 1)) * 96 + (j & 1) * 16) * 8);
#pragma unroll 1
        for (int r = r0 + (GBLIND + GR / 2) * 96; r < n0 + 16; r += 96) {
            cp_async16_lt(sb + SM_EA + r * 32 + (lane & 1) * 16, geb + lds32(sb + SM_EG + r * 8), r, n0);
            cp_async16_lt(sb + SM_EA + r * 32 + 512 + (lane & 1) * 16, geb + lds32(sb + SM_EG + r * 8 + 128), r + 16, n0);
        }
        bar_sync(10, 640);
#pragma unroll
        for (int j = 0; j < GR; j++) rc[j].y = lds32(sm + MI_NREC + 4 + ((rc[j].y >> 11) & 1016u));
#pragma unroll
        for (int ph = 0; ph < 2; ph++) {
#pragma unroll
            for (int j = 0; j < GR; j++) {
                const int r = r0 + (GBLIND + (j >> 1)) * 96 + (j & 1) * 16;
                cp_async16_lt(sb + SM_EA + r * 32 + (lane & 1) * 16, geb + rc[j].x, ((rc[j].y != 0u) == (ph == 0)) ? r : n0, n0);
            }
            asm volatile("cp.async.mbarrier.arrive.noinc.shared::cta.b64 [%0];" ::"r"(sm + MI_MB + 24 - ph * 8) : "memory");
            if (ph == 0 && tid == 544) STAMP(10);
        }
        if (tid == 544) {
            STAMP(12);
            tma_store_wait();
            tma_load(sb + SM_W, &tm_wu, 0, 0, sm + MI_MB + 8);
            tma_load(sb + SM_W + 16384, &tm_wu, 64, 0, sm + MI_MB + 8);
        }
        __syncwarp();
        bar_sync(11, 640);
    } else {
        __syncwarp();
#pragma unroll 1
        for (int it = 0; it < SPIN_LIMIT; it++) {
            if (!__any_sync(0xffffffffu, (int)((v0.w ^ parw) | (v1.w ^ parw)) < 0)) break;
            v0 = ldg128_rlx(bp);
            if (wg < 4) v1 = ldg128_rlx(bp + (size_t)68 * G * SEGCAP);
        }
        if (tid == 0) STAMP(8);
        const uint32_t lt = (1u << lane) - 1u;
        uint32_t en[8] = {v0.x, v1.x, v0.y, v1.y, v0.z, v1.z, W_EMPTY, W_EMPTY}, es[8], gb = 0;
        int gt = 0;
        auto count = [&](int i) {
            const uint32_t m = __ballot_sync(0xffffffffu, en[i] != W_EMPTY);
            es[i] = gt + __popc(m & lt);
            gt += __popc(m);
        };
        auto put = [&](int i) {
            const uint32_t el = en[i] >> 21;
            sts64_lt(sb + SM_EG + (gb + es[i]) * 8, (el + (el >> 5) * (G * 32 - 32) + ((tid >> 3) + (i & 1) * 68) * 32) * 32, en[i], en[i], W_EMPTY);
        };
#pragma unroll
        for (int i = 0; i < 6; i++) count(i);
        const bool deep = __any_sync(0xffffffffu, (v0.w & v1.w & T_EMPTY) != T_EMPTY);
        if (deep) {
#pragma unroll
            for (int r = 0; r < 2; r++) {
                const uint32_t tl = (r ? v1.w : v0.w) & T_EMPTY, er = tl >> 14, el = ((er >> 4) * 52429u) >> 18;
                if (tl == T_OVF) sts32(sm + MI_SLOW, 1);
                if (tl < T_OVF) en[6 + r] = (el << 21) | ((er - el * ROWS) << 14) | (tl & 16383u);
                count(6 + r);
            }
        }
        if (lane == 0) gb = atoms_add(sm + MI_ECNT, gt);
        gb = __shfl_sync(0xffffffffu, gb, 0);
        if (gb + gt > EAROWS || gt > 128) { sts32(sm + MI_SLOW, 1); gb = 0; gt = 0; }
#pragma unroll
        for (int i = 0; i < 6; i++) put(i);
        if (deep) { put(6); put(7); }
        __syncwarp();
        bar_arrive(6, 640);
        uint32_t rec[4], rk[4];
#pragma unroll
        for (int j = 0; j < 4; j++) rec[j] = lds32(sb + SM_EG + (gb + lane) * 8 + 4 + j * 256);
#pragma unroll
        for (int j = 0; j < 4; j++) {
            if (lane + 32 * j >= gt) rec[j] = W_EMPTY;
            rk[j] = 0;
            if (32 * j < gt) rk[j] = atoms_add_lt(sm + MI_KEY + ((rec[j] >> 12) & 508u), 128, rec[j], W_EMPTY);
        }
        bar_sync(9, 544);
        if (tid == 0) STAMP(9);
        if (warp < 10) {
            const uint32_t key = lds32(sm + MI_KEY + (tid >> 2) * 4);
            uint4 o[5];
#pragma unroll
            for (int i = 0; i < 5; i++) o[i] = lds128(sm + MI_KEY + (tid & 3) * 80 + i * 16);
            uint32_t sp = 0, sq = 0;
#pragma unroll
            for (int i = 0; i < 5; i++) {
                sp += (key - o[i].x) >> 31; sq += (key - o[i].y) >> 31;
                sp += (key - o[i].z) >> 31; sq += (key - o[i].w) >> 31;
            }
            sp += sq;
            sp += __shfl_xor_sync(0xffffffffu, sp, 1);
            sp += __shfl_xor_sync(0xffffffffu, sp, 2);
            const int grp = 9 - (int)(sp >> 3);
            const bool down = grp < 5;
            const uint32_t tp = grp * 8 + (sp & 7);
            sts32_lt(sm + MI_PERM + tp * 4, tid >> 2, tid & 3, 1);
            sts32_lt(sm + MI_SKEY + sp * 4, key, tid & 3, 1);
            sts64_lt(sm + MI_NREC + tid * 2, boundary(down ? grp : 9 - grp) * 16 + (sp & 7) * 2 + (down ? -14 : 0),
                     down ? ~0u : sp < 4 ? 1u : 0u, tid & 3, 1);
        }
        bar_arrive(10, 640);
        bar_sync(9, 544);
        if (tid == 0) STAMP(25);
        {
            uint2 nr[4];
#pragma unroll
            for (int j = 0; j < 4; j++) nr[j] = lds64(sm + MI_NREC + ((rec[j] >> 11) & 1016u));
            const uint32_t cap = split_cap(sm) << 7;
#pragma unroll
            for (int j = 0; j < 4; j++) {
                if (nr[j].y == 1u) {
                    nr[j].y = 0u;
                    if (rk[j] >= cap) { rk[j] -= cap; nr[j].x -= 6; nr[j].y = ~0u; }
                }
                const uint32_t off = ((rk[j] >> 4) & ~15u) | ((rk[j] >> 7) & 1u);
                const uint32_t ps = min(nr[j].x + (off ^ nr[j].y), (uint32_t)TRASH);
                sts32(sb + SM_LIST + ps * 4, rec[j] & 16383u);
                sts32(sb + SM_EL + ps * 4, sb + SM_EA + (gb + lane + 32 * j) * 32);
            }
        }
        if (tid == 0) STAMP(11);
        bar_arrive(11, 640);
        bar_sync(9, 544);
    }
    if (tid == 0) STAMP(13);

    Consts k;
    k.w3[0] = lds128(sb + SM_W3G + f * 1024 + lane * 16);
    k.w3[1] = lds128(sb + SM_W3G + f * 1024 + 512 + lane * 16);
    k.par = tag;
    k.q8 = q * 8;
    k.pb = reinterpret_cast<const unsigned char*>(gP) + f * 64 + q * 16;
    int dm;
    bool slow;
    {
        const int l = min(lane, 9);
        const int cap = split_cap(sm);
        dm = lds32(sm + MI_SKEY + (9 - l) * 32) >> 7;
        if (l == 0) dm = max(dm, (int)(lds32(sm + MI_SKEY) >> 7) - cap);
        if (l == 9) dm = cap;
        const int nt = (dm + 1) >> 1;
        const int other = __shfl_sync(0xffffffffu, nt, (10 - l) % 10);
        const int lim = l == 0 ? 16 : l == 5 ? 24 : (l == 1 || l == 9) ? 37 : 21;
        slow = __any_sync(0xffffffffu, nt + other > lim) || lds32(sm + MI_SLOW) != 0;
    }
    if (slow) {
        k.id = lds128(sm + MI_ID + lane * 16);
        mbar_wait0(sm + MI_MB + 16);
        slow_path(sb, e_attr, src, dst, E, k);
    } else {
        const int tsw = (int)__reduce_max_sync(0xffffffffu, (uint32_t)boundary(wg));
        const int dA = (int)__reduce_max_sync(0xffffffffu, lane == wg ? dm : 0);
        const int dB = (int)__reduce_max_sync(0xffffffffu, lane == 9 - wg ? dm : 0);
        const int t = tsw - ((dA + 1) >> 1);
        const uint32_t la = sb + SM_LIST + g * 8;
        k.id = lds128(sm + MI_ID + lane * 16);
        float qi[2][4], acc[2][4];
        {
            const uint2 r = lds64(sm + MI_PERM + wg * 32 + q * 8 + ((wg == 0 && q >= 2) ? 272 : 0));
            load_q(qi, sb, r.x, r.y, f, g);
        }
#pragma unroll
        for (int i = 0; i < 8; i++) (&acc[0][0])[i] = 0.f;
        Tile x0, y0;
        fetch(x0, la + t * 64, k);
        uint2 en = lds64(la + t * 64 + 64), eo = lds64(la + (SM_EL - SM_LIST) + t * 64);
        auto group_switch = [&]() {
            flush_agg(tile_addr(sb + SM_AGG, lds32(sm + MI_PERM + wg * 32 + g * 4), 4 * f + q), acc);
            const uint2 r = lds64(sm + MI_PERM + (9 - wg) * 32 + q * 8);
            load_q(qi, sb, r.x, r.y, f, g);
#pragma unroll
            for (int i = 0; i < 8; i++) {
                const float v = __shfl_xor_sync(0xffffffffu, (&acc[0][0])[i], 2);
                (&acc[0][0])[i] = (wg == 0 && q < 2) ? v : 0.f;
            }
        };
        mbar_wait0(sm + MI_MB + 24);
        if (tid == 0) STAMP(27);
        uint32_t lp = la + t * 64;
        auto step = [&](Tile& st, Tile& nx) {
            const uint2 ea0 = lds64(eo.x | k.q8), ea1 = lds64(eo.y | k.q8);
            if (__builtin_expect(stale(st, st, k), 0)) {
#pragma unroll 1
                for (int it = 0; it < SPIN_LIMIT; it++) {
                    fetch(st, lp, k);
                    if (!stale(st, st, k)) break;
                }
            }
            nx.p0 = ldg128_rlx(k.pb + (size_t)en.x * 256);
            nx.p1 = ldg128_rlx(k.pb + (size_t)en.y * 256);
            en = lds64(lp + 128);
            eo = lds64(lp + (SM_EL - SM_LIST) + 64);
            float c[2][2][4];
#pragma unroll
            for (int u = 0; u < 2; u++) {
                mma16_c(c[u][0], k.id.x, k.id.y, k.id.z, k.id.w, u ? st.p0.z : st.p0.x, u ? st.p0.w : st.p0.y, qi[u]);
                mma16_c(c[u][1], k.id.x, k.id.y, k.id.z, k.id.w, u ? st.p1.z : st.p1.x, u ? st.p1.w : st.p1.y, qi[u]);
            }
#pragma unroll
            for (int u = 0; u < 2; u++) {
                mma16(c[u][0], k.w3[u].x, k.w3[u].y, k.w3[u].z, k.w3[u].w, ea0.x, ea0.y);
                mma16(c[u][1], k.w3[u].x, k.w3[u].y, k.w3[u].z, k.w3[u].w, ea1.x, ea1.y);
            }
#pragma unroll
            for (int u = 0; u < 2; u++)
#pragma unroll
                for (int n = 0; n < 2; n++)
#pragma unroll
                    for (int i = 0; i < 4; i++) acc[u][i] += silu_half(c[u][n][i]);
            lp += 64;
        };
        auto revalidate = [&]() {
            if (__builtin_expect(stale(x0, x0, k), 0)) {
#pragma unroll 1
                for (int it = 0; it < SPIN_LIMIT; it++) {
                    fetch(x0, lp, k);
                    if (!stale(x0, x0, k)) break;
                }
            }
        };
        auto half = [&](const uint4& p, uint2 ea) {
            float c[2][4];
#pragma unroll
            for (int u = 0; u < 2; u++) mma16_c(c[u], k.id.x, k.id.y, k.id.z, k.id.w, u ? p.z : p.x, u ? p.w : p.y, qi[u]);
#pragma unroll
            for (int u = 0; u < 2; u++) mma16(c[u], k.w3[u].x, k.w3[u].y, k.w3[u].z, k.w3[u].w, ea.x, ea.y);
#pragma unroll
            for (int u = 0; u < 2; u++)
#pragma unroll
                for (int i = 0; i < 4; i++) acc[u][i] += silu_half(c[u][i]);
        };
        if (dA & 1) {
            const uint2 ea = lds64(eo.y | k.q8);
            revalidate();
            const uint4 p = x0.p1;
            x0.p0 = ldg128_rlx(k.pb + (size_t)en.x * 256);
            x0.p1 = ldg128_rlx(k.pb + (size_t)en.y * 256);
            en = lds64(lp + 128);
            eo = lds64(lp + (SM_EL - SM_LIST) + 64);
            half(p, ea);
            lp += 64;
        }
        int rem = dA >> 1;
#pragma unroll 1
        for (int ph = 0; ph < 2; ph++) {
#pragma unroll 1
            for (; rem >= 2; rem -= 2) {
                step(x0, y0);
                step(y0, x0);
            }
            if (rem) {
                step(x0, y0);
                x0 = y0;
            }
            if (ph == 0) {
                group_switch();
                mbar_wait0(sm + MI_MB + 16);
                __syncwarp();
                rem = dB >> 1;
            }
        }
        if (dB & 1) {
            const uint2 ea = lds64(eo.x | k.q8);
            revalidate();
            half(x0.p0, ea);
        }
        flush_agg(tile_addr(sb + SM_AGG, lds32(sm + MI_PERM + (9 - wg) * 32 + g * 4), 4 * f + q), acc);
    }
    if (lane == 0 && f == 0) STAMP(14 + wg);

    fence_async();
    __syncwarp();
    if (lane == 0) asm volatile("mbarrier.arrive.shared::cta.b64 _, [%0];" ::"r"(sm + MI_MB + 32) : "memory");
    bar_sync(5 + wg, 128);
    if ((tid & 127) == 0) sts32(sm + MI_SEG + wg * 4, atoms_add(sm + MI_TICKET, 1));
    bar_sync(5 + wg, 128);
    const int role = (int)__reduce_max_sync(0xffffffffu, lds32(sm + MI_SEG + wg * 4));
    if (role == 4) return;
    {
        const int half = role >> 1, h = role & 1;
        float acc[20];
        const uint64_t da = make_desc(sb + SM_W + h * 16384);
        mbar_wait0(sm + MI_MB + 8);
        wg_fence();
        {
            const uint64_t db = make_desc(sb + SM_XS + half * 5120);
#pragma unroll
            for (int ks = 0; ks < 8; ks++) wgmma_n40(acc, da + ks * 128, db + (ks >> 2) * 640 + (ks & 3) * 2, ks);
        }
        wg_commit();
        mbar_wait0(sm + MI_MB + 32);
        __syncwarp();
        if (role == 3 && (tid & 127) == 0) STAMP(19);
        wg_fence();
        {
            const uint64_t db = make_desc(sb + SM_AGG + half * 5120);
#pragma unroll
            for (int ks = 0; ks < 8; ks++) wgmma_n40(acc, da + 2048 + ks * 128, db + (ks >> 2) * 640 + (ks & 3) * 2, 1);
        }
        wg_commit();
        const int t2 = tid & 127, r8 = t2 >> 3, c8 = t2 & 7;
        wg_wait<0>();
        if (role == 3 && (tid & 127) == 0) STAMP(20);
        const uint32_t ot = sb + SM_EA + role * 6144;
        {
            const int mi = lane >> 3, r = lane & 7;
            const uint32_t a = ot + ((mi >> 1) * 8 + r) * 128 + (((f * 2 + (mi & 1)) ^ r) << 4);
            uint32_t v[10];
#pragma unroll
            for (int i = 0; i < 10; i++) v[i] = pack_bf16(silu_half(0.5f * acc[2 * i]), silu_half(0.5f * acc[2 * i + 1]));
            stsm_x4_trans(a, v[0], v[1], v[2], v[3]);
            stsm_x4_trans(a + 2048, v[4], v[5], v[6], v[7]);
            stsm_x2_trans(a + 4096, v[8], v[9]);
        }
        bar_sync(5 + wg, 128);
        {
            const int lim = min(min(N - cta * NPC, NPC) - half * 40, 40);
            __nv_bfloat16* op = out + (size_t)(cta * NPC + half * 40 + r8) * D + h * 64 + c8 * 8;
            uint4 v[3];
#pragma unroll
            for (int p = 0; p < 3; p++) v[p] = lds128(ot + r8 * 128 + ((c8 ^ (r8 & 7)) << 4) + p * 2048);
#pragma unroll
            for (int p = 0; p < 3; p++)
                if (r8 + 16 * p < lim) stg128(op + 16 * p * D, v[p]);
        }
        if (role == 3 && (tid & 127) == 0) STAMP(21);
    }
}

__global__ void fb_zero(int n) {
    for (int i = blockIdx.x * blockDim.x + threadIdx.x; i < n; i += gridDim.x * blockDim.x) g_aggf[i] = 0.f;
}
__global__ void fb_edge(const __nv_bfloat16* x, const __nv_bfloat16* e_attr, const int* src, const int* dst,
                        const __nv_bfloat16* w_msg, int E) {
    __shared__ float in[2 * D + DE];
    for (int e = blockIdx.x; e < E; e += gridDim.x) {
        int s = src[e], d = dst[e], c = threadIdx.x;
        __syncthreads();
        in[c] = __bfloat162float(x[(size_t)s * D + c]);
        in[D + c] = __bfloat162float(x[(size_t)d * D + c]);
        if (c < DE) in[2 * D + c] = __bfloat162float(e_attr[(size_t)e * DE + c]);
        __syncthreads();
        float a = 0.f;
        for (int k = 0; k < 2 * D + DE; k++) a = fmaf(in[k], __bfloat162float(w_msg[k * D + c]), a);
        atomicAdd(&g_aggf[(size_t)d * D + c], a / (1.f + __expf(-a)));
    }
}
__global__ void fb_node(const __nv_bfloat16* x, const __nv_bfloat16* w_upd, __nv_bfloat16* out, int N) {
    __shared__ float in[2 * D];
    for (int n = blockIdx.x; n < N; n += gridDim.x) {
        int c = threadIdx.x;
        __syncthreads();
        in[c] = __bfloat162float(x[(size_t)n * D + c]);
        in[D + c] = g_aggf[(size_t)n * D + c];
        __syncthreads();
        float a = 0.f;
        for (int k = 0; k < 2 * D; k++) a = fmaf(in[k], __bfloat162float(w_upd[k * D + c]), a);
        out[(size_t)n * D + c] = __float2bfloat16(a / (1.f + __expf(-a)));
    }
}

}

extern "C" void kernel_launch(void* const* d_in, const int* in_sizes, int n_in, void* d_out, int out_size) {
    const __nv_bfloat16* x = (const __nv_bfloat16*)d_in[0];
    const __nv_bfloat16* e_attr = (const __nv_bfloat16*)d_in[1];
    const int* src = (const int*)d_in[2];
    const int* dst = (const int*)d_in[3];
    const __nv_bfloat16* w_msg = (const __nv_bfloat16*)d_in[4];
    const __nv_bfloat16* w_upd = (const __nv_bfloat16*)d_in[5];
    __nv_bfloat16* out = (__nv_bfloat16*)d_out;
    const int N = in_sizes[0] / D, E = in_sizes[2];

    typedef CUresult (*EncodeFn)(CUtensorMap*, CUtensorMapDataType, cuuint32_t, void*, const cuuint64_t*, const cuuint64_t*,
                                 const cuuint32_t*, const cuuint32_t*, CUtensorMapInterleave, CUtensorMapSwizzle,
                                 CUtensorMapL2promotion, CUtensorMapFloatOOBfill);
    static int mode = -1;
    static void *pP = nullptr, *pSeg = nullptr, *pEp = nullptr;
    static EncodeFn encode = nullptr;
    if (mode < 0) {
        int dev = 0, sms = 0, nb = 0;
        cudaGetDevice(&dev);
        cudaDeviceGetAttribute(&sms, cudaDevAttrMultiProcessorCount, dev);
        cudaError_t e = cudaFuncSetAttribute(mpnn_kernel, cudaFuncAttributeMaxDynamicSharedMemorySize, SM_ALLOC);
        if (e == cudaSuccess) e = cudaOccupancyMaxActiveBlocksPerMultiprocessor(&nb, mpnn_kernel, NT, SM_ALLOC);
        if (e == cudaSuccess) e = cudaGetSymbolAddress(&pP, g_P);
        if (e == cudaSuccess) e = cudaGetSymbolAddress(&pSeg, g_seg);
        if (e == cudaSuccess) e = cudaGetSymbolAddress(&pEp, g_epoch);
        void* fn = nullptr;
        cudaDriverEntryPointQueryResult qr;
        if (e == cudaSuccess) e = cudaGetDriverEntryPoint("cuTensorMapEncodeTiled", &fn, cudaEnableDefault, &qr);
        encode = (EncodeFn)fn;
        mode = (e == cudaSuccess && nb >= 1 && sms >= G && encode != nullptr) ? 1 : 0;
        (void)cudaGetLastError();
    }
    bool fast = mode == 1 && N >= 1 && N <= NMAX && E <= EMAX && (E & 1) == 0;
    CUtensorMap tm[5];
    if (fast) {
        void* base[5] = {(void*)x, (void*)w_msg, (void*)w_upd, pP, (void*)out};
        const cuuint64_t rows[5] = {(cuuint64_t)N, 2 * D + DE, 2 * D, NMAX, (cuuint64_t)N};
        const cuuint32_t boxr[5] = {ROWS, 128, 128, NPC, NPC};
        for (int i = 0; i < 4 && fast; i++) {
            const cuuint64_t dims[2] = {D, rows[i]}, strides[1] = {D * 2};
            const cuuint32_t box[2] = {64, boxr[i]}, es[2] = {1, 1};
            fast = encode(&tm[i], CU_TENSOR_MAP_DATA_TYPE_BFLOAT16, 2, base[i], dims, strides, box, es, CU_TENSOR_MAP_INTERLEAVE_NONE,
                          CU_TENSOR_MAP_SWIZZLE_128B, CU_TENSOR_MAP_L2_PROMOTION_NONE, CU_TENSOR_MAP_FLOAT_OOB_FILL_NONE) == CUDA_SUCCESS;
        }
    }
    if (fast) {
        mpnn_kernel<<<G, NT, SM_ALLOC, cudaStreamPerThread>>>(e_attr, src, dst, w_msg, w_upd, out, (__nv_bfloat16*)pP, (uint32_t*)pSeg,
                                                              (unsigned long long*)pEp, N, E, tm[0], tm[1], tm[2], tm[3]);
    } else {
        fb_zero<<<256, 256, 0, cudaStreamPerThread>>>(N * D);
        fb_edge<<<2048, D, 0, cudaStreamPerThread>>>(x, e_attr, src, dst, w_msg, E);
        fb_node<<<2048, D, 0, cudaStreamPerThread>>>(x, w_upd, out, N);
    }
}
```

```cpp
#include <cuda.h>
#include <cuda_runtime.h>
#include <cuda_bf16.h>
#include <stdint.h>

namespace {

constexpr int D = 128;
constexpr int DE = 16;
constexpr int G = 132;
constexpr int NPC = 76;
constexpr int ROWS = 80;
constexpr int EPC = 1216;
constexpr int NT = 640;
constexpr int NMAX = G * NPC;
constexpr int EMAX = G * EPC;
constexpr int SEGCAP = 32;

constexpr int NTILE = 120;
constexpr int SM_XS = 0;
constexpr int SM_W = 20480;
constexpr int SM_AGG = SM_W + 65536;
constexpr int EAROWS = 1536;
constexpr int SM_EA = SM_AGG + 20480;
constexpr int SM_LIST = SM_EA + EAROWS * 32;
constexpr int TRASH = (NTILE + 4) * 16;
constexpr int SM_EL = SM_LIST + 8000;
constexpr int SM_EG = SM_EL + 8000;
constexpr int SM_W3F = SM_EG + 13312;
constexpr int SM_W3G = SM_W3F + 4096;
constexpr int SM_MISC = SM_W3G + 4096;
constexpr int SM_STG = SM_AGG;
constexpr int SM_TOTAL = SM_MISC + 3328;
constexpr int SM_ALLOC = SM_TOTAL + 1024;
constexpr int MI_SEG = 0;
constexpr int MI_SLOW = 544;
constexpr int MI_ECNT = 548;
constexpr int MI_TICKET = 552;
constexpr int MI_KEY = 560;
constexpr int MI_MB = 3264;
constexpr int MI_TAG = 1072;
constexpr int MI_PERM = 1088;
constexpr int MI_SKEY = 1408;
constexpr int MI_NREC = 1728;
constexpr int MI_ID = 2752;

constexpr uint32_t W_EMPTY = 0xFFFFFFFFu;
constexpr uint32_t T_EMPTY = 0x7FFFFFFFu;
constexpr uint32_t T_OVF = 0x7FFFBFFFu;
constexpr int GBLIND = 4;
constexpr int HSLACK = 66;
constexpr int SPIN_LIMIT = 1 << 20;

__device__ __align__(256) __nv_bfloat16 g_P[(NMAX + G) * D];
__device__ __align__(256) uint32_t g_seg[G * G * SEGCAP];
__device__ __align__(256) unsigned long long g_epoch[32];
__device__ float g_aggf[4 * 1024 * 1024];
#define STAMP(i) do { } while (0)

__device__ __forceinline__ uint32_t smem_u32(const void* p) { return (uint32_t)__cvta_generic_to_shared(p); }
__device__ __forceinline__ void fence_async() { asm volatile("fence.proxy.async.shared::cta;" ::: "memory"); }
__device__ __forceinline__ void bar_sync(int id, int n) { asm volatile("bar.sync %0, %1;" ::"r"(id), "r"(n) : "memory"); }
__device__ __forceinline__ void bar_arrive(int id, int n) { asm volatile("bar.arrive %0, %1;" ::"r"(id), "r"(n) : "memory"); }
__device__ __forceinline__ uint32_t lds32(uint32_t a) { uint32_t v; asm volatile("ld.shared.u32 %0, [%1];" : "=r"(v) : "r"(a) : "memory"); return v; }
__device__ __forceinline__ uint2 lds64(uint32_t a) { uint2 v; asm volatile("ld.shared.v2.u32 {%0,%1}, [%2];" : "=r"(v.x), "=r"(v.y) : "r"(a) : "memory"); return v; }
__device__ __forceinline__ uint4 lds128(uint32_t a) { uint4 v; asm volatile("ld.shared.v4.u32 {%0,%1,%2,%3}, [%4];" : "=r"(v.x), "=r"(v.y), "=r"(v.z), "=r"(v.w) : "r"(a) : "memory"); return v; }
__device__ __forceinline__ void sts32(uint32_t a, uint32_t v) { asm volatile("st.shared.u32 [%0], %1;" ::"r"(a), "r"(v) : "memory"); }
__device__ __forceinline__ void sts128(uint32_t a, uint4 v) { asm volatile("st.shared.v4.u32 [%0], {%1,%2,%3,%4};" ::"r"(a), "r"(v.x), "r"(v.y), "r"(v.z), "r"(v.w) : "memory"); }
__device__ __forceinline__ void sts32_lt(uint32_t a, uint32_t v, uint32_t x, uint32_t lim) {
    asm volatile("{\n.reg .pred p;\nsetp.lt.u32 p, %2, %3;\n@p st.shared.u32 [%0], %1;\n}" ::"r"(a), "r"(v), "r"(x), "r"(lim) : "memory");
}
__device__ __forceinline__ void sts64_lt(uint32_t a, uint32_t v, uint32_t w, uint32_t x, uint32_t lim) {
    asm volatile("{\n.reg .pred p;\nsetp.lt.u32 p, %3, %4;\n@p st.shared.v2.u32 [%0], {%1, %2};\n}" ::"r"(a), "r"(v), "r"(w), "r"(x), "r"(lim) : "memory");
}
__device__ __forceinline__ void cp_async16_lt(uint32_t dst, const void* src, int x, int lim) {
    asm volatile("{\n.reg .pred p;\nsetp.lt.s32 p, %2, %3;\n@p cp.async.cg.shared.global [%0], [%1], 16;\n}" ::"r"(dst), "l"(src), "r"(x), "r"(lim) : "memory");
}
__device__ __forceinline__ uint32_t atoms_add_lt(uint32_t a, int d, uint32_t x, uint32_t lim) {
    uint32_t v = 0;
    asm volatile("{\n.reg .pred p;\nsetp.lt.u32 p, %3, %4;\n@p atom.shared.add.u32 %0, [%1], %2;\n}" : "+r"(v) : "r"(a), "r"(d), "r"(x), "r"(lim) : "memory");
    return v;
}
__device__ __forceinline__ uint32_t atoms_add(uint32_t a, int d) { uint32_t v; asm volatile("atom.shared.add.u32 %0, [%1], %2;" : "=r"(v) : "r"(a), "r"(d) : "memory"); return v; }
__device__ __forceinline__ uint4 ldg128(const void* p) { uint4 v; asm volatile("ld.global.v4.u32 {%0,%1,%2,%3}, [%4];" : "=r"(v.x), "=r"(v.y), "=r"(v.z), "=r"(v.w) : "l"(p) : "memory"); return v; }
__device__ __forceinline__ uint2 ldg64(const void* p) { uint2 v; asm volatile("ld.global.v2.u32 {%0,%1}, [%2];" : "=r"(v.x), "=r"(v.y) : "l"(p) : "memory"); return v; }
__device__ __forceinline__ void sts64(uint32_t a, uint32_t x, uint32_t y) { asm volatile("st.shared.v2.u32 [%0], {%1,%2};" ::"r"(a), "r"(x), "r"(y) : "memory"); }
__device__ __forceinline__ void stg128(void* p, uint4 v) { asm volatile("st.global.v4.u32 [%0], {%1,%2,%3,%4};" ::"l"(p), "r"(v.x), "r"(v.y), "r"(v.z), "r"(v.w) : "memory"); }
__device__ __forceinline__ uint32_t pack_bf16(float lo, float hi) {
    uint32_t r; asm("cvt.rn.bf16x2.f32 %0, %1, %2;" : "=r"(r) : "f"(hi), "f"(lo)); return r;
}
__device__ __forceinline__ float tanh_fast(float x) { float r; asm("tanh.approx.f32 %0, %1;" : "=f"(r) : "f"(x)); return r; }
__device__ __forceinline__ float silu_half(float h) { return fmaf(h, tanh_fast(h), h); }
__device__ __forceinline__ uint32_t movm(uint32_t a) { uint32_t d; asm volatile("movmatrix.sync.aligned.m8n8.trans.b16 %0, %1;" : "=r"(d) : "r"(a)); return d; }
__device__ __forceinline__ uint32_t shl_clamp(uint32_t v, uint32_t s) { uint32_t d; asm("shl.b32 %0, %1, %2;" : "=r"(d) : "r"(v), "r"(s)); return d; }
__device__ __forceinline__ void mma16(float (&d)[4], uint32_t a0, uint32_t a1, uint32_t a2, uint32_t a3, uint32_t b0, uint32_t b1) {
    asm("mma.sync.aligned.m16n8k16.row.col.f32.bf16.bf16.f32 {%0,%1,%2,%3}, {%4,%5,%6,%7}, {%8,%9}, {%0,%1,%2,%3};"
        : "+f"(d[0]), "+f"(d[1]), "+f"(d[2]), "+f"(d[3]) : "r"(a0), "r"(a1), "r"(a2), "r"(a3), "r"(b0), "r"(b1));
}
__device__ __forceinline__ void mma16_c(float (&d)[4], uint32_t a0, uint32_t a1, uint32_t a2, uint32_t a3, uint32_t b0, uint32_t b1, const float (&c)[4]) {
    asm("mma.sync.aligned.m16n8k16.row.col.f32.bf16.bf16.f32 {%0,%1,%2,%3}, {%4,%5,%6,%7}, {%8,%9}, {%10,%11,%12,%13};"
        : "=f"(d[0]), "=f"(d[1]), "=f"(d[2]), "=f"(d[3]) : "r"(a0), "r"(a1), "r"(a2), "r"(a3), "r"(b0), "r"(b1),
          "f"(c[0]), "f"(c[1]), "f"(c[2]), "f"(c[3]));
}
__device__ __forceinline__ void stsm_x4_trans(uint32_t addr, uint32_t r0, uint32_t r1, uint32_t r2, uint32_t r3) {
    asm volatile("stmatrix.sync.aligned.m8n8.x4.trans.shared.b16 [%0], {%1,%2,%3,%4};" ::"r"(addr), "r"(r0), "r"(r1), "r"(r2), "r"(r3) : "memory");
}

__device__ __forceinline__ uint64_t make_desc(uint32_t addr) {
    return (uint64_t)((addr & 0x3FFFF) >> 4) | ((uint64_t)64 << 16) | ((uint64_t)64 << 32) | ((uint64_t)1 << 62);
}
__device__ __forceinline__ void wg_fence() { asm volatile("wgmma.fence.sync.aligned;" ::: "memory"); }
__device__ __forceinline__ void wg_commit() { asm volatile("wgmma.commit_group.sync.aligned;" ::: "memory"); }
template <int N> __device__ __forceinline__ void wg_wait() { asm volatile("wgmma.wait_group.sync.aligned %0;" ::"n"(N) : "memory"); }
__device__ __forceinline__ void wgmma_n80(float (&d)[40], uint64_t da, uint64_t db, int scale_d) {
    asm volatile(
        "{\n.reg .pred p;\nsetp.ne.b32 p, %42, 0;\n"
        "wgmma.mma_async.sync.aligned.m64n80k16.f32.bf16.bf16 "
        "{%0,%1,%2,%3,%4,%5,%6,%7,%8,%9,%10,%11,%12,%13,%14,%15,%16,%17,%18,%19,"
        "%20,%21,%22,%23,%24,%25,%26,%27,%28,%29,%30,%31,%32,%33,%34,%35,%36,%37,%38,%39}, "
        "%40, %41, p, 1, 1, 1, 0;\n}\n"
        : "+f"(d[0]), "+f"(d[1]), "+f"(d[2]), "+f"(d[3]), "+f"(d[4]), "+f"(d[5]), "+f"(d[6]), "+f"(d[7]), "+f"(d[8]), "+f"(d[9]),
          "+f"(d[10]), "+f"(d[11]), "+f"(d[12]), "+f"(d[13]), "+f"(d[14]), "+f"(d[15]), "+f"(d[16]), "+f"(d[17]), "+f"(d[18]), "+f"(d[19]),
          "+f"(d[20]), "+f"(d[21]), "+f"(d[22]), "+f"(d[23]), "+f"(d[24]), "+f"(d[25]), "+f"(d[26]), "+f"(d[27]), "+f"(d[28]), "+f"(d[29]),
          "+f"(d[30]), "+f"(d[31]), "+f"(d[32]), "+f"(d[33]), "+f"(d[34]), "+f"(d[35]), "+f"(d[36]), "+f"(d[37]), "+f"(d[38]), "+f"(d[39])
        : "l"(da), "l"(db), "r"(scale_d));
}

__device__ __forceinline__ void wgmma_n40(float (&d)[20], uint64_t da, uint64_t db, int scale_d) {
    asm volatile(
        "{\n.reg .pred p;\nsetp.ne.b32 p, %22, 0;\n"
        "wgmma.mma_async.sync.aligned.m64n40k16.f32.bf16.bf16 "
        "{%0,%1,%2,%3,%4,%5,%6,%7,%8,%9,%10,%11,%12,%13,%14,%15,%16,%17,%18,%19}, "
        "%20, %21, p, 1, 1, 1, 0;\n}\n"
        : "+f"(d[0]), "+f"(d[1]), "+f"(d[2]), "+f"(d[3]), "+f"(d[4]), "+f"(d[5]), "+f"(d[6]), "+f"(d[7]), "+f"(d[8]), "+f"(d[9]),
          "+f"(d[10]), "+f"(d[11]), "+f"(d[12]), "+f"(d[13]), "+f"(d[14]), "+f"(d[15]), "+f"(d[16]), "+f"(d[17]), "+f"(d[18]), "+f"(d[19])
        : "l"(da), "l"(db), "r"(scale_d));
}
__device__ __forceinline__ void stsm_x2_trans(uint32_t addr, uint32_t r0, uint32_t r1) {
    asm volatile("stmatrix.sync.aligned.m8n8.x2.trans.shared.b16 [%0], {%1,%2};" ::"r"(addr), "r"(r0), "r"(r1) : "memory");
}
__device__ __forceinline__ uint4 ldg128_rlx(const void* p) { uint4 v; asm volatile("ld.relaxed.gpu.global.v4.u32 {%0,%1,%2,%3}, [%4];" : "=r"(v.x), "=r"(v.y), "=r"(v.z), "=r"(v.w) : "l"(p) : "memory"); return v; }
__device__ __forceinline__ void stg128_rlx(void* p, uint4 v) { asm volatile("st.relaxed.gpu.global.v4.u32 [%0], {%1,%2,%3,%4};" ::"l"(p), "r"(v.x), "r"(v.y), "r"(v.z), "r"(v.w) : "memory"); }

__device__ __forceinline__ unsigned long long ldg64_rlx(const void* p) { unsigned long long v; asm volatile("ld.relaxed.gpu.global.u64 %0, [%1];" : "=l"(v) : "l"(p) : "memory"); return v; }
__device__ __forceinline__ void hint_arrive(unsigned long long* p) { asm volatile("red.relaxed.gpu.global.add.u64 [%0], 1;" ::"l"(p) : "memory"); }
__device__ __forceinline__ void hint_wait(const unsigned long long* p, unsigned long long target) {
#pragma unroll 1
    for (int it = 0; it < SPIN_LIMIT; it++)
        if (ldg64_rlx(p) >= target) break;
}

__host__ __device__ constexpr int boundary(int k) { return k == 0 ? 8 : 24 + 21 * k; }
__device__ __forceinline__ uint32_t tile_addr(uint32_t base, int row, int c) {
    return base + (c >> 3) * 10240 + row * 128 + (((c & 7) ^ (row & 7)) << 4);
}

__device__ __forceinline__ uint32_t split_cap(uint32_t sm) {
    const int d0 = lds32(sm + MI_SKEY) >> 7, d4 = lds32(sm + MI_SKEY + 16) >> 7, d72 = lds32(sm + MI_SKEY + 288) >> 7;
    return max(d4, d0 - ((d72 + 1) & ~1));
}

struct Tile { uint4 p0, p1; };
struct Consts { uint4 w3[2]; uint4 id; uint32_t par, q8; const unsigned char* pb; };

__device__ __forceinline__ void fetch(Tile& st, uint32_t la, const Consts& k) {
    uint2 e = lds64(la);
    st.p0 = ldg128_rlx(k.pb + (size_t)e.x * 256);
    st.p1 = ldg128_rlx(k.pb + (size_t)e.y * 256);
}
__device__ __forceinline__ bool stale(const Tile& a, const Tile& b, const Consts& k) {
    uint32_t t, u;
    asm("lop3.b32 %0, %1, %2, %3, 0x7E;" : "=r"(t) : "r"(a.p0.x), "r"(a.p1.x), "r"(k.par));
    asm("lop3.b32 %0, %1, %2, %3, 0x7E;" : "=r"(u) : "r"(b.p0.x), "r"(b.p1.x), "r"(k.par));
    asm("lop3.b32 %0, %1, %2, 1, 0xA8;" : "=r"(t) : "r"(t), "r"(u));
    return __any_sync(0xffffffffu, t != 0);
}
__device__ __forceinline__ void validate(Tile& a, Tile& b, uint32_t la, const Consts& k) {
    if (__builtin_expect(stale(a, b, k), 0)) {
#pragma unroll 1
        for (int it = 0; it < SPIN_LIMIT; it++) {
            fetch(a, la, k);
            fetch(b, la + 64, k);
            if (!stale(a, b, k)) break;
        }
    }
}
__device__ __forceinline__ void tile_mma(float (&acc)[2][4], const Tile& st, uint2 eo, const float (&qi)[2][4], const Consts& k) {
    const uint2 ea0 = lds64(eo.x | k.q8), ea1 = lds64(eo.y | k.q8);
    float c[2][2][4];
#pragma unroll
    for (int u = 0; u < 2; u++) {
        mma16_c(c[u][0], k.id.x, k.id.y, k.id.z, k.id.w, u ? st.p0.z : st.p0.x, u ? st.p0.w : st.p0.y, qi[u]);
        mma16_c(c[u][1], k.id.x, k.id.y, k.id.z, k.id.w, u ? st.p1.z : st.p1.x, u ? st.p1.w : st.p1.y, qi[u]);
    }
#pragma unroll
    for (int u = 0; u < 2; u++) {
        mma16(c[u][0], k.w3[u].x, k.w3[u].y, k.w3[u].z, k.w3[u].w, ea0.x, ea0.y);
        mma16(c[u][1], k.w3[u].x, k.w3[u].y, k.w3[u].z, k.w3[u].w, ea1.x, ea1.y);
    }
#pragma unroll
    for (int u = 0; u < 2; u++)
#pragma unroll
        for (int n = 0; n < 2; n++)
#pragma unroll
            for (int i = 0; i < 4; i++) acc[u][i] += silu_half(c[u][n][i]);
}
__device__ __forceinline__ void load_q(float (&qi)[2][4], uint32_t sb, int ra, int rb, int f, int g) {
    const uint4 a = lds128(tile_addr(sb + SM_AGG, ra, 4 * f + (g >> 1))), b = lds128(tile_addr(sb + SM_AGG, rb, 4 * f + (g >> 1)));
    const uint32_t sel = (g & 1) ? 0x3244u : 0x1044u;
    qi[0][0] = 0.5f * __uint_as_float(__byte_perm(a.x, 0, sel)); qi[0][1] = 0.5f * __uint_as_float(__byte_perm(b.x, 0, sel));
    qi[0][2] = 0.5f * __uint_as_float(__byte_perm(a.y, 0, sel)); qi[0][3] = 0.5f * __uint_as_float(__byte_perm(b.y, 0, sel));
    qi[1][0] = 0.5f * __uint_as_float(__byte_perm(a.z, 0, sel)); qi[1][1] = 0.5f * __uint_as_float(__byte_perm(b.z, 0, sel));
    qi[1][2] = 0.5f * __uint_as_float(__byte_perm(a.w, 0, sel)); qi[1][3] = 0.5f * __uint_as_float(__byte_perm(b.w, 0, sel));
}
__device__ __forceinline__ void flush_agg(uint32_t addr, const float (&acc)[2][4]) {
    uint4 v;
    v.x = movm(pack_bf16(acc[0][0], acc[0][1]));
    v.y = movm(pack_bf16(acc[0][2], acc[0][3]));
    v.z = movm(pack_bf16(acc[1][0], acc[1][1]));
    v.w = movm(pack_bf16(acc[1][2], acc[1][3]));
    sts128(addr, v);
}

__device__ __forceinline__ void tma_load(uint32_t dst, const CUtensorMap* tm, int c0, int c1, uint32_t mbar) {
    asm volatile("cp.async.bulk.tensor.2d.shared::cluster.global.mbarrier::complete_tx::bytes [%0], [%1, {%2, %3}], [%4];"
                 ::"r"(dst), "l"(tm), "r"(c0), "r"(c1), "r"(mbar) : "memory");
}
__device__ __forceinline__ void tma_store(const CUtensorMap* tm, int c0, int c1, uint32_t src) {
    asm volatile("cp.async.bulk.tensor.2d.global.shared::cta.bulk_group [%0, {%1, %2}], [%3];" ::"l"(tm), "r"(c0), "r"(c1), "r"(src) : "memory");
    asm volatile("cp.async.bulk.commit_group;" ::: "memory");
}
__device__ __forceinline__ void tma_store_wait() { asm volatile("cp.async.bulk.wait_group.read 0;" ::: "memory"); }
__device__ __forceinline__ void mbar_wait0(uint32_t a) {
    for (int it = 0; it < SPIN_LIMIT; it++) {
        uint32_t ok;
        asm volatile("{\n.reg .pred p;\nmbarrier.try_wait.parity.shared::cta.b64 p, [%1], 0;\nselp.u32 %0, 1, 0, p;\n}" : "=r"(ok) : "r"(a) : "memory");
        if (ok) break;
    }
}

__device__ __noinline__ void slow_path(uint32_t sb, const __nv_bfloat16* e_attr, const int* src, const int* dst, int E, Consts k) {
    const int tid = threadIdx.x, lane = tid & 31, wg = tid >> 7, f = (tid >> 5) & 3, g = lane >> 2, q = lane & 3, cta = blockIdx.x;
    const uint32_t s_deg = sb + SM_MISC + MI_KEY;
    float acc[2][2][4];
    for (int i = 0; i < 16; i++) (&acc[0][0][0])[i] = 0.f;
    int scan = 0, state = 0, row = 0;
    bool more = true;
    while (more) {
        more = false;
        __syncthreads();
        if (tid < ROWS) sts32(s_deg + tid * 4, 0);
        for (int i = tid; i < EAROWS * 2; i += NT) sts128(sb + SM_EA + i * 16, make_uint4(0, 0, 0, 0));
        for (int i = tid; i < (NTILE + 4) * 16; i += NT) sts32(sb + SM_LIST + i * 4, NMAX + cta);
        __syncthreads();
        while (true) {
            const int e = scan + tid;
            if (state == 0) {
                state = 2;
                if (e < E) {
                    int dn = dst[e];
                    if (dn / NPC == cta) { state = 1; row = dn - cta * NPC; }
                }
            }
            if (state == 1) {
                uint32_t rank = atoms_add(s_deg + row * 4, 1);
                if (rank < 18) {
                    uint32_t pos = ((row >> 3) * 9 + (rank >> 1)) * 16 + (row & 7) * 2 + (rank & 1);
                    sts32(sb + SM_LIST + pos * 4, (uint32_t)src[e]);
                    sts128(sb + SM_EA + pos * 32, ldg128(e_attr + (size_t)e * DE));
                    sts128(sb + SM_EA + pos * 32 + 16, ldg128(e_attr + (size_t)e * DE + 8));
                    state = 2;
                }
            }
            if (__syncthreads_or(state == 1)) { more = true; break; }
            scan += NT;
            state = 0;
            if (scan >= E) break;
        }
#pragma unroll
        for (int b = 0; b < 2; b++) {
            const int grp = 2 * wg + b;
            const int mx = min((int)__reduce_max_sync(0xffffffffu, lds32(s_deg + (grp * 8 + g) * 4)), 18);
            float qi[2][4];
            load_q(qi, sb, grp * 8 + 2 * q, grp * 8 + 2 * q + 1, f, g);
            for (int t = 0; t * 2 < mx; t++) {
                const int tile = grp * 9 + t;
                Tile st, s2;
                const uint32_t la = sb + SM_LIST + tile * 64 + g * 8;
                fetch(st, la, k);
                fetch(s2, la + 64, k);
                validate(st, s2, la, k);
                tile_mma(acc[b], st, make_uint2(sb + SM_EA + tile * 512 + g * 64, sb + SM_EA + tile * 512 + g * 64 + 32), qi, k);
            }
        }
    }
    __syncwarp();
    flush_agg(tile_addr(sb + SM_AGG, wg * 16 + g, 4 * f + q), acc[0]);
    flush_agg(tile_addr(sb + SM_AGG, wg * 16 + 8 + g, 4 * f + q), acc[1]);
}

__global__ void __launch_bounds__(NT, 1)
mpnn_kernel(const __nv_bfloat16* __restrict__ e_attr, const int* __restrict__ src, const int* __restrict__ dst,
            const __nv_bfloat16* __restrict__ w_msg, const __nv_bfloat16* __restrict__ w_upd,
            __nv_bfloat16* __restrict__ out, __nv_bfloat16* __restrict__ gP, uint32_t* __restrict__ gseg,
            unsigned long long* __restrict__ gepoch, int N, int E,
            const __grid_constant__ CUtensorMap tm_x, const __grid_constant__ CUtensorMap tm_wm,
            const __grid_constant__ CUtensorMap tm_wu, const __grid_constant__ CUtensorMap tm_p) {
    extern __shared__ unsigned char smem_raw[];
    const uint32_t sb = (smem_u32(smem_raw) + 1023u) & ~1023u;
    const int tid = threadIdx.x, warp = tid >> 5, lane = tid & 31;
    const int wg = warp >> 2, f = warp & 3, g = lane >> 2, q = lane & 3;
    const int cta = blockIdx.x;
    const int wgu = (int)__reduce_max_sync(0xffffffffu, (uint32_t)wg);
    const uint32_t sm = sb + SM_MISC;
    if (tid == 0) STAMP(0);

    uint2 d2 = make_uint2(~0u, 0), s2;
    {
        const int e0 = ((tid >> 4) * G + cta) * 32 + (tid & 15) * 2;
        if (tid < EPC / 2 && e0 < E) {
            d2 = ldg64(dst + e0);
            s2 = ldg64(src + e0);
        }
    }
    unsigned long long cnt0 = 0;
    if (tid == 576) cnt0 = ldg64_rlx(gepoch);
    sts128(sb + SM_STG + tid * 16, make_uint4(W_EMPTY, W_EMPTY, W_EMPTY, W_EMPTY));
    if (tid < 416) sts128(sb + SM_STG + 10240 + tid * 16, make_uint4(W_EMPTY, W_EMPTY, W_EMPTY, W_EMPTY));
    else if (tid < 636) sts32(sm + (tid - 416) * 4, tid >= 556 ? 127 - (tid - 556) : tid == 553);
    if (warp == 19) {
        if (lane == 31) {
            asm volatile("mbarrier.init.shared::cta.b64 [%0], 1;" ::"r"(sm + MI_MB) : "memory");
            asm volatile("mbarrier.init.shared::cta.b64 [%0], 1;" ::"r"(sm + MI_MB + 8) : "memory");
            asm volatile("mbarrier.init.shared::cta.b64 [%0], 96;" ::"r"(sm + MI_MB + 16) : "memory");
            asm volatile("mbarrier.init.shared::cta.b64 [%0], 96;" ::"r"(sm + MI_MB + 24) : "memory");
            asm volatile("mbarrier.init.shared::cta.b64 [%0], 20;" ::"r"(sm + MI_MB + 32) : "memory");
            sts64(sm + MI_NREC + 127 * 8, 0x40000000u, 0u);
        }
        __syncwarp();
        bar_arrive(3, 640);
        if (lane == 31) {
            fence_async();
            asm volatile("mbarrier.arrive.expect_tx.shared::cta.b64 _, [%0], %1;" ::"r"(sm + MI_MB), "r"(20480 + 65536 + 4096) : "memory");
            asm volatile("mbarrier.arrive.expect_tx.shared::cta.b64 _, [%0], %1;" ::"r"(sm + MI_MB + 8), "r"(65536) : "memory");
#pragma unroll
            for (int b = 0; b < 4; b++) tma_load(sb + SM_W + b * 16384, &tm_wm, (b & 1) * 64, (b >> 1) * 128, sm + MI_MB);
            asm volatile("cp.async.bulk.shared::cluster.global.mbarrier::complete_tx::bytes [%0], [%1], 4096, [%2];"
                         ::"r"(sb + SM_W3F), "l"(w_msg + 2 * D * D), "r"(sm + MI_MB) : "memory");
            tma_load(sb + SM_XS, &tm_x, 0, cta * NPC, sm + MI_MB);
            tma_load(sb + SM_XS + 10240, &tm_x, 64, cta * NPC, sm + MI_MB);
            asm volatile("prefetch.tensormap [%0];" ::"l"(&tm_p) : "memory");
            asm volatile("prefetch.tensormap [%0];" ::"l"(&tm_wu) : "memory");
        }
        __syncwarp();
    } else {
        bar_sync(3, 640);
    }
    if (tid == 0) STAMP(23);
    if (tid >= 636)
        asm volatile("prefetch.global.L2 [%0];" ::"l"(reinterpret_cast<const unsigned char*>(w_upd) + min(cta * 4 + (tid - 636), 511) * 128));
    if (d2.x != ~0u) {
        const uint32_t dc0 = d2.x / NPC, dc1 = d2.y / NPC;
        const uint32_t r0 = atoms_add(sm + MI_SEG + dc0 * 4, 1), r1 = atoms_add(sm + MI_SEG + dc1 * 4, 1);
        const uint32_t w0 = s2.x | (((tid << 8) + d2.x - dc0 * NPC) << 14), w1 = s2.y | (((tid << 8) + 128 + d2.y - dc1 * NPC) << 14);
        sts32_lt(sb + SM_STG + dc0 * 128 + (r0 & 7) * 16 + (r0 >> 3) * 4, w0, r0, SEGCAP);
        sts32_lt(sb + SM_STG + dc1 * 128 + (r1 & 7) * 16 + (r1 >> 3) * 4, w1, r1, SEGCAP);
    }
    if (tid == 576) {
        cnt0 = cnt0 / G + 1;
        sts64(sm + MI_TAG, (uint32_t)cnt0, (uint32_t)(cnt0 >> 32));
    }
    if (tid == 0) STAMP(24);
    __syncthreads();
    const uint32_t tag = lds32(sm + MI_TAG);
    const uint32_t parw = tag << 31;
    {
        uint4 v[2];
        uint32_t cn[2];
#pragma unroll
        for (int i = 0; i < 2; i++) {
            v[i] = lds128(sb + SM_STG + tid * 16 + i * 10240);
            cn[i] = lds32(sm + MI_SEG + min((tid >> 3) + i * 80, 135) * 4);
        }
#pragma unroll
        for (int i = 0; i < 2; i++) {
            uint32_t tl = T_EMPTY;
            if (cn[i] > 24) {
                const uint32_t w = v[i].w;
                if (w != W_EMPTY) tl = (((w >> 21) * ROWS + ((w >> 14) & 127u)) << 14) | (w & 16383u);
                if (cn[i] > SEGCAP) tl = T_OVF;
            }
            v[i].w = tl | parw;
            if (i == 0 || tid < 416) stg128_rlx(gseg + (size_t)cta * (G * SEGCAP) + tid * 4 + i * 2560, v[i]);
        }
    }
    const uint32_t* bp = gseg + ((size_t)(tid >> 3) * G + cta) * SEGCAP + (tid & 7) * 4;
    uint4 v1 = make_uint4(W_EMPTY, W_EMPTY, W_EMPTY, T_EMPTY | parw), v0 = v1;
    auto prefill2 = [&]() {
        const uint32_t pr = NMAX + cta;
        if (tid < 496) sts128(sb + SM_LIST + tid * 16, make_uint4(pr, pr, pr, pr));
        if (tid >= 144) sts128(sb + SM_EL + (tid - 144) * 16, make_uint4(sb + SM_EA, sb + SM_EA, sb + SM_EA, sb + SM_EA));
        else if (tid >= 142) sts128(sb + SM_EA + (tid - 142) * 16, make_uint4(0, 0, 0, 0));
        else if (tid < 32) {
            uint32_t idf = shl_clamp(0x3F00u, (uint32_t)((g - 2 * q) << 4));
            sts128(sm + MI_ID + lane * 16, make_uint4(idf, 0, 0, idf));
        }
    };
    const uint32_t so = (((lane >> 4) & 1) * 8 + (lane & 7)) * 128 + (((f * 2 + ((lane >> 3) & 1)) ^ (lane & 7)) << 4);
    if (wgu < 2) {
        bar_arrive(2, 640);
        prefill2();
        mbar_wait0(sm + MI_MB);
        if (tid == 0) STAMP(1);
        if (tid == 255) {
            int eb = cta * EPC, ne = min(EPC, E - eb);
            if (ne > 0) asm volatile("cp.async.bulk.prefetch.L2.global [%0], %1;" ::"l"(e_attr + (size_t)eb * DE), "r"(ne * 32) : "memory");
        }
        float gacc[40];
        const uint64_t da = make_desc(sb + SM_W + wgu * 16384), db = make_desc(sb + SM_XS);
        wg_fence();
#pragma unroll
        for (int ks = 0; ks < 8; ks++) wgmma_n80(gacc, da + ks * 128, db + (ks >> 2) * 640 + (ks & 3) * 2, ks);
        wg_commit();
        const uint32_t keep = g == 0 ? 0xFFFEFFFEu : 0xFFFFFFFFu, setb = g == 0 ? (tag & 1u) * 0x10001u : 0u;
        wg_wait<0>();
        if (tid == 0) STAMP(2);
        bar_sync(7 + wg, 128);
#pragma unroll
        for (int j = 0; j < 5; j++)
            stsm_x4_trans(sb + SM_W + wg * 16384 + so + j * 2048,
                          (pack_bf16(gacc[8 * j], gacc[8 * j + 1]) & keep) | setb, (pack_bf16(gacc[8 * j + 2], gacc[8 * j + 3]) & keep) | setb,
                          (pack_bf16(gacc[8 * j + 4], gacc[8 * j + 5]) & keep) | setb, (pack_bf16(gacc[8 * j + 6], gacc[8 * j + 7]) & keep) | setb);
        fence_async();
        bar_arrive(5, 544);
        bar_sync(12, 288);
        if (tid == 0) STAMP(22);
        v0 = ldg128_rlx(bp);
        v1 = ldg128_rlx(bp + (size_t)68 * G * SEGCAP);
    } else if (wgu < 4) {
        bar_arrive(2, 640);
        prefill2();
        bar_sync(4, 384);
        v0 = ldg128_rlx(bp);
        v1 = ldg128_rlx(bp + (size_t)68 * G * SEGCAP);
        float gacc[40];
        const uint64_t da = make_desc(sb + SM_W + wgu * 16384), db = make_desc(sb + SM_XS);
        mbar_wait0(sm + MI_MB);
        __syncwarp();
        wg_fence();
#pragma unroll
        for (int ks = 0; ks < 8; ks++) wgmma_n80(gacc, da + ks * 128, db + (ks >> 2) * 640 + (ks & 3) * 2, ks);
        wg_commit();
        wg_wait<0>();
#pragma unroll
        for (int j = 0; j < 5; j++)
            stsm_x4_trans(sb + SM_AGG + (wg - 2) * 10240 + so + j * 2048,
                          pack_bf16(gacc[8 * j], gacc[8 * j + 1]), pack_bf16(gacc[8 * j + 2], gacc[8 * j + 3]),
                          pack_bf16(gacc[8 * j + 4], gacc[8 * j + 5]), pack_bf16(gacc[8 * j + 6], gacc[8 * j + 7]));
        bar_arrive(5, 544);
    } else {
        if (warp < 19) bar_arrive(2, 640);
        prefill2();
        if (tid >= 624)
            stg128_rlx(gP + (size_t)(NMAX + cta) * D + (tid - 624) * 8, make_uint4(0xFF00FF00u | (tag & 1u), 0xFF00FF00u, 0xFF00FF00u, 0xFF00FF00u));
        if (warp == 19) {
            bar_sync(2, 640);
            if (lane == 0) { STAMP(4); hint_arrive(gepoch); hint_wait(gepoch, (((unsigned long long)lds32(sm + MI_TAG + 4) << 32) | tag) * G - HSLACK); STAMP(7); }
            __syncwarp();
            bar_arrive(12, 288);
        } else {
            mbar_wait0(sm + MI_MB);
#pragma unroll 1
            for (int ff = f; ff < 4; ff += 3) {
                const uint32_t wa = sb + SM_W3F + (4 * q * D + 32 * ff + (g >> 1) * 8 + (g & 1)) * 2;
                uint32_t w[8];
#pragma unroll
                for (int i = 0; i < 8; i++) {
                    const int u = i >> 2, r = i & 3, o = 4 * u + 2 * (r & 1) + 2 * (r >> 1) * D;
                    unsigned short lo, hi;
                    asm volatile("ld.shared.u16 %0, [%1];" : "=h"(lo) : "r"(wa + o * 2));
                    asm volatile("ld.shared.u16 %0, [%1];" : "=h"(hi) : "r"(wa + (o + D) * 2));
                    asm("mul.bf16x2 %0, %1, %2;" : "=r"(w[i]) : "r"((uint32_t)lo | ((uint32_t)hi << 16)), "r"(0x3F003F00u));
                }
                sts128(sb + SM_W3G + ff * 1024 + lane * 16, make_uint4(w[0], w[1], w[2], w[3]));
                sts128(sb + SM_W3G + ff * 1024 + 512 + lane * 16, make_uint4(w[4], w[5], w[6], w[7]));
            }
        }
        bar_sync(4, 384);
        if (warp == 16) v0 = ldg128_rlx(bp);
    }
    if (warp >= 17) {
        if (warp == 17) {
            bar_sync(5, 544);
            if (lane == 0) {
                tma_store(&tm_p, 0, cta * NPC, sb + SM_W);
                tma_store(&tm_p, 64, cta * NPC, sb + SM_W + 16384);
                tma_load(sb + SM_W + 32768, &tm_wu, 0, 128, sm + MI_MB + 8);
                tma_load(sb + SM_W + 49152, &tm_wu, 64, 128, sm + MI_MB + 8);
                STAMP(3);
            }
            __syncwarp();
        }
        bar_sync(6, 640);
        const int n = min((int)lds32(sm + MI_ECNT), EAROWS);
        const unsigned char* geb = reinterpret_cast<const unsigned char*>(e_attr) + (lane & 1) * 16;
        const int n0 = lds32(sm + MI_SLOW) == 0 ? n : 0;
        const int r0 = 1 + (lane >> 1) + (warp - 17) * 32;
#pragma unroll
        for (int it = 0; it < GBLIND; it++)
#pragma unroll
            for (int j = 0; j < 2; j++) {
                const int r = r0 + it * 96 + j * 16;
                cp_async16_lt(sb + SM_EA + r * 32 + (lane & 1) * 16, geb + lds32(sb + SM_EG + r * 8), r, n0);
            }
        constexpr int GR = 28 - 2 * GBLIND;
        uint2 rc[GR];
#pragma unroll
        for (int j = 0; j < GR; j++) rc[j] = lds64(sb + SM_EG + (r0 + (GBLIND + (j >> 1)) * 96 + (j & 1) * 16) * 8);
#pragma unroll 1
        for (int r = r0 + (GBLIND + GR / 2) * 96; r < n0 + 16; r += 96) {
            cp_async16_lt(sb + SM_EA + r * 32 + (lane & 1) * 16, geb + lds32(sb + SM_EG + r * 8), r, n0);
            cp_async16_lt(sb + SM_EA + r * 32 + 512 + (lane & 1) * 16, geb + lds32(sb + SM_EG + r * 8 + 128), r + 16, n0);
        }
        bar_sync(10, 640);
#pragma unroll
        for (int j = 0; j < GR; j++) rc[j].y = lds32(sm + MI_NREC + 4 + ((rc[j].y >> 11) & 1016u));
#pragma unroll
        for (int ph = 0; ph < 2; ph++) {
#pragma unroll
            for (int j = 0; j < GR; j++) {
                const int r = r0 + (GBLIND + (j >> 1)) * 96 + (j & 1) * 16;
                cp_async16_lt(sb + SM_EA + r * 32 + (lane & 1) * 16, geb + rc[j].x, ((rc[j].y != 0u) == (ph == 0)) ? r : n0, n0);
            }
            asm volatile("cp.async.mbarrier.arrive.noinc.shared::cta.b64 [%0];" ::"r"(sm + MI_MB + 24 - ph * 8) : "memory");
            if (ph == 0 && tid == 544) STAMP(10);
        }
        if (tid == 544) {
            STAMP(12);
            tma_store_wait();
            tma_load(sb + SM_W, &tm_wu, 0, 0, sm + MI_MB + 8);
            tma_load(sb + SM_W + 16384, &tm_wu, 64, 0, sm + MI_MB + 8);
        }
        __syncwarp();
        bar_sync(11, 640);
    } else {
        __syncwarp();
#pragma unroll 1
        for (int it = 0; it < SPIN_LIMIT; it++) {
            if (!__any_sync(0xffffffffu, (int)((v0.w ^ parw) | (v1.w ^ parw)) < 0)) break;
            if (it) __nanosleep(200);
            v0 = ldg128_rlx(bp);
            if (wg < 4) v1 = ldg128_rlx(bp + (size_t)68 * G * SEGCAP);
        }
        if (tid == 0) STAMP(8);
        const uint32_t lt = (1u << lane) - 1u;
        uint32_t en[8] = {v0.x, v1.x, v0.y, v1.y, v0.z, v1.z, W_EMPTY, W_EMPTY}, es[8], gb = 0;
        int gt = 0;
        auto count = [&](int i) {
            const uint32_t m = __ballot_sync(0xffffffffu, en[i] != W_EMPTY);
            es[i] = gt + __popc(m & lt);
            gt += __popc(m);
        };
        auto put = [&](int i) {
            const uint32_t el = en[i] >> 21;
            sts64_lt(sb + SM_EG + (gb + es[i]) * 8, (el + (el >> 5) * (G * 32 - 32) + ((tid >> 3) + (i & 1) * 68) * 32) * 32, en[i], en[i], W_EMPTY);
        };
#pragma unroll
        for (int i = 0; i < 6; i++) count(i);
        const bool deep = __any_sync(0xffffffffu, (v0.w & v1.w & T_EMPTY) != T_EMPTY);
        if (deep) {
#pragma unroll
            for (int r = 0; r < 2; r++) {
                const uint32_t tl = (r ? v1.w : v0.w) & T_EMPTY, er = tl >> 14, el = ((er >> 4) * 52429u) >> 18;
                if (tl == T_OVF) sts32(sm + MI_SLOW, 1);
                if (tl < T_OVF) en[6 + r] = (el << 21) | ((er - el * ROWS) << 14) | (tl & 16383u);
                count(6 + r);
            }
        }
        if (lane == 0) gb = atoms_add(sm + MI_ECNT, gt);
        gb = __shfl_sync(0xffffffffu, gb, 0);
        if (gb + gt > EAROWS || gt > 128) { sts32(sm + MI_SLOW, 1); gb = 0; gt = 0; }
#pragma unroll
        for (int i = 0; i < 6; i++) put(i);
        if (deep) { put(6); put(7); }
        __syncwarp();
        bar_arrive(6, 640);
        uint32_t rec[4], rk[4];
#pragma unroll
        for (int j = 0; j < 4; j++) rec[j] = lds32(sb + SM_EG + (gb + lane) * 8 + 4 + j * 256);
#pragma unroll
        for (int j = 0; j < 4; j++) {
            if (lane + 32 * j >= gt) rec[j] = W_EMPTY;
            rk[j] = 0;
            if (32 * j < gt) rk[j] = atoms_add_lt(sm + MI_KEY + ((rec[j] >> 12) & 508u), 128, rec[j], W_EMPTY);
        }
        bar_sync(9, 544);
        if (tid == 0) STAMP(9);
        if (warp < 10) {
            const uint32_t key = lds32(sm + MI_KEY + (tid >> 2) * 4);
            uint4 o[5];
#pragma unroll
            for (int i = 0; i < 5; i++) o[i] = lds128(sm + MI_KEY + (tid & 3) * 80 + i * 16);
            uint32_t sp = 0, sq = 0;
#pragma unroll
            for (int i = 0; i < 5; i++) {
                sp += (key - o[i].x) >> 31; sq += (key - o[i].y) >> 31;
                sp += (key - o[i].z) >> 31; sq += (key - o[i].w) >> 31;
            }
            sp += sq;
            sp += __shfl_xor_sync(0xffffffffu, sp, 1);
            sp += __shfl_xor_sync(0xffffffffu, sp, 2);
            const int grp = 9 - (int)(sp >> 3);
            const bool down = grp < 5;
            const uint32_t tp = grp * 8 + (sp & 7);
            sts32_lt(sm + MI_PERM + tp * 4, tid >> 2, tid & 3, 1);
            sts32_lt(sm + MI_SKEY + sp * 4, key, tid & 3, 1);
            sts64_lt(sm + MI_NREC + tid * 2, boundary(down ? grp : 9 - grp) * 16 + (sp & 7) * 2 + (down ? -14 : 0),
                     down ? ~0u : sp < 4 ? 1u : 0u, tid & 3, 1);
        }
        bar_arrive(10, 640);
        bar_sync(9, 544);
        if (tid == 0) STAMP(25);
        {
            uint2 nr[4];
#pragma unroll
            for (int j = 0; j < 4; j++) nr[j] = lds64(sm + MI_NREC + ((rec[j] >> 11) & 1016u));
            const uint32_t cap = split_cap(sm) << 7;
#pragma unroll
            for (int j = 0; j < 4; j++) {
                if (nr[j].y == 1u) {
                    nr[j].y = 0u;
                    if (rk[j] >= cap) { rk[j] -= cap; nr[j].x -= 6; nr[j].y = ~0u; }
                }
                const uint32_t off = ((rk[j] >> 4) & ~15u) | ((rk[j] >> 7) & 1u);
                const uint32_t ps = min(nr[j].x + (off ^ nr[j].y), (uint32_t)TRASH);
                sts32(sb + SM_LIST + ps * 4, rec[j] & 16383u);
                sts32(sb + SM_EL + ps * 4, sb + SM_EA + (gb + lane + 32 * j) * 32);
            }
        }
        if (tid == 0) STAMP(11);
        bar_arrive(11, 640);
        bar_sync(9, 544);
    }
    if (tid == 0) STAMP(13);

    Consts k;
    k.w3[0] = lds128(sb + SM_W3G + f * 1024 + lane * 16);
    k.w3[1] = lds128(sb + SM_W3G + f * 1024 + 512 + lane * 16);
    k.par = tag;
    k.q8 = q * 8;
    k.pb = reinterpret_cast<const unsigned char*>(gP) + f * 64 + q * 16;
    int dm;
    bool slow;
    {
        const int l = min(lane, 9);
        const int cap = split_cap(sm);
        dm = lds32(sm + MI_SKEY + (9 - l) * 32) >> 7;
        if (l == 0) dm = max(dm, (int)(lds32(sm + MI_SKEY) >> 7) - cap);
        if (l == 9) dm = cap;
        const int nt = (dm + 1) >> 1;
        const int other = __shfl_sync(0xffffffffu, nt, (10 - l) % 10);
        const int lim = l == 0 ? 16 : l == 5 ? 24 : (l == 1 || l == 9) ? 37 : 21;
        slow = __any_sync(0xffffffffu, nt + other > lim) || lds32(sm + MI_SLOW) != 0;
    }
    if (slow) {
        k.id = lds128(sm + MI_ID + lane * 16);
        mbar_wait0(sm + MI_MB + 16);
        slow_path(sb, e_attr, src, dst, E, k);
    } else {
        const int tsw = (int)__reduce_max_sync(0xffffffffu, (uint32_t)boundary(wg));
        const int dA = (int)__reduce_max_sync(0xffffffffu, lane == wg ? dm : 0);
        const int dB = (int)__reduce_max_sync(0xffffffffu, lane == 9 - wg ? dm : 0);
        const int t = tsw - ((dA + 1) >> 1);
        const uint32_t la = sb + SM_LIST + g * 8;
        k.id = lds128(sm + MI_ID + lane * 16);
        float qi[2][4], acc[2][4];
        {
            const uint2 r = lds64(sm + MI_PERM + wg * 32 + q * 8 + ((wg == 0 && q >= 2) ? 272 : 0));
            load_q(qi, sb, r.x, r.y, f, g);
        }
#pragma unroll
        for (int i = 0; i < 8; i++) (&acc[0][0])[i] = 0.f;
        Tile x0, y0;
        fetch(x0, la + t * 64, k);
        uint2 en = lds64(la + t * 64 + 64), eo = lds64(la + (SM_EL - SM_LIST) + t * 64);
        auto group_switch = [&]() {
            flush_agg(tile_addr(sb + SM_AGG, lds32(sm + MI_PERM + wg * 32 + g * 4), 4 * f + q), acc);
            const uint2 r = lds64(sm + MI_PERM + (9 - wg) * 32 + q * 8);
            load_q(qi, sb, r.x, r.y, f, g);
#pragma unroll
            for (int i = 0; i < 8; i++) {
                const float v = __shfl_xor_sync(0xffffffffu, (&acc[0][0])[i], 2);
                (&acc[0][0])[i] = (wg == 0 && q < 2) ? v : 0.f;
            }
        };
        mbar_wait0(sm + MI_MB + 24);
        if (tid == 0) STAMP(27);
        uint32_t lp = la + t * 64;
        auto step = [&](Tile& st, Tile& nx) {
            const uint2 ea0 = lds64(eo.x | k.q8), ea1 = lds64(eo.y | k.q8);
            if (__builtin_expect(stale(st, st, k), 0)) {
#pragma unroll 1
                for (int it = 0; it < SPIN_LIMIT; it++) {
                    fetch(st, lp, k);
                    if (!stale(st, st, k)) break;
                }
            }
            nx.p0 = ldg128_rlx(k.pb + (size_t)en.x * 256);
            nx.p1 = ldg128_rlx(k.pb + (size_t)en.y * 256);
            en = lds64(lp + 128);
            eo = lds64(lp + (SM_EL - SM_LIST) + 64);
            float c[2][2][4];
#pragma unroll
            for (int u = 0; u < 2; u++) {
                mma16_c(c[u][0], k.id.x, k.id.y, k.id.z, k.id.w, u ? st.p0.z : st.p0.x, u ? st.p0.w : st.p0.y, qi[u]);
                mma16_c(c[u][1], k.id.x, k.id.y, k.id.z, k.id.w, u ? st.p1.z : st.p1.x, u ? st.p1.w : st.p1.y, qi[u]);
            }
#pragma unroll
            for (int u = 0; u < 2; u++) {
                mma16(c[u][0], k.w3[u].x, k.w3[u].y, k.w3[u].z, k.w3[u].w, ea0.x, ea0.y);
                mma16(c[u][1], k.w3[u].x, k.w3[u].y, k.w3[u].z, k.w3[u].w, ea1.x, ea1.y);
            }
#pragma unroll
            for (int u = 0; u < 2; u++)
#pragma unroll
                for (int n = 0; n < 2; n++)
#pragma unroll
                    for (int i = 0; i < 4; i++) acc[u][i] += silu_half(c[u][n][i]);
            lp += 64;
        };
        auto revalidate = [&]() {
            if (__builtin_expect(stale(x0, x0, k), 0)) {
#pragma unroll 1
                for (int it = 0; it < SPIN_LIMIT; it++) {
                    fetch(x0, lp, k);
                    if (!stale(x0, x0, k)) break;
                }
            }
        };
        auto half = [&](const uint4& p, uint2 ea) {
            float c[2][4];
#pragma unroll
            for (int u = 0; u < 2; u++) mma16_c(c[u], k.id.x, k.id.y, k.id.z, k.id.w, u ? p.z : p.x, u ? p.w : p.y, qi[u]);
#pragma unroll
            for (int u = 0; u < 2; u++) mma16(c[u], k.w3[u].x, k.w3[u].y, k.w3[u].z, k.w3[u].w, ea.x, ea.y);
#pragma unroll
            for (int u = 0; u < 2; u++)
#pragma unroll
                for (int i = 0; i < 4; i++) acc[u][i] += silu_half(c[u][i]);
        };
        if (dA & 1) {
            const uint2 ea = lds64(eo.y | k.q8);
            revalidate();
            const uint4 p = x0.p1;
            x0.p0 = ldg128_rlx(k.pb + (size_t)en.x * 256);
            x0.p1 = ldg128_rlx(k.pb + (size_t)en.y * 256);
            en = lds64(lp + 128);
            eo = lds64(lp + (SM_EL - SM_LIST) + 64);
            half(p, ea);
            lp += 64;
        }
        int rem = dA >> 1;
#pragma unroll 1
        for (int ph = 0; ph < 2; ph++) {
#pragma unroll 1
            for (; rem >= 2; rem -= 2) {
                step(x0, y0);
                step(y0, x0);
            }
            if (rem) {
                step(x0, y0);
                x0 = y0;
            }
            if (ph == 0) {
                group_switch();
                mbar_wait0(sm + MI_MB + 16);
                __syncwarp();
                rem = dB >> 1;
            }
        }
        if (dB & 1) {
            const uint2 ea = lds64(eo.x | k.q8);
            revalidate();
            half(x0.p0, ea);
        }
        flush_agg(tile_addr(sb + SM_AGG, lds32(sm + MI_PERM + (9 - wg) * 32 + g * 4), 4 * f + q), acc);
    }
    if (lane == 0 && f == 0) STAMP(14 + wg);

    fence_async();
    __syncwarp();
    if (lane == 0) asm volatile("mbarrier.arrive.shared::cta.b64 _, [%0];" ::"r"(sm + MI_MB + 32) : "memory");
    bar_sync(5 + wg, 128);
    if ((tid & 127) == 0) sts32(sm + MI_SEG + wg * 4, atoms_add(sm + MI_TICKET, 1));
    bar_sync(5 + wg, 128);
    const int role = (int)__reduce_max_sync(0xffffffffu, lds32(sm + MI_SEG + wg * 4));
    if (role == 4) return;
    {
        const int half = role >> 1, h = role & 1;
        float acc[20];
        const uint64_t da = make_desc(sb + SM_W + h * 16384);
        mbar_wait0(sm + MI_MB + 8);
        wg_fence();
        {
            const uint64_t db = make_desc(sb + SM_XS + half * 5120);
#pragma unroll
            for (int ks = 0; ks < 8; ks++) wgmma_n40(acc, da + ks * 128, db + (ks >> 2) * 640 + (ks & 3) * 2, ks);
        }
        wg_commit();
        mbar_wait0(sm + MI_MB + 32);
        __syncwarp();
        if (role == 3 && (tid & 127) == 0) STAMP(19);
        wg_fence();
        {
            const uint64_t db = make_desc(sb + SM_AGG + half * 5120);
#pragma unroll
            for (int ks = 0; ks < 8; ks++) wgmma_n40(acc, da + 2048 + ks * 128, db + (ks >> 2) * 640 + (ks & 3) * 2, 1);
        }
        wg_commit();
        const int t2 = tid & 127, r8 = t2 >> 3, c8 = t2 & 7;
        wg_wait<0>();
        if (role == 3 && (tid & 127) == 0) STAMP(20);
        const uint32_t ot = sb + SM_EA + role * 6144;
        {
            const int mi = lane >> 3, r = lane & 7;
            const uint32_t a = ot + ((mi >> 1) * 8 + r) * 128 + (((f * 2 + (mi & 1)) ^ r) << 4);
            uint32_t v[10];
#pragma unroll
            for (int i = 0; i < 10; i++) v[i] = pack_bf16(silu_half(0.5f * acc[2 * i]), silu_half(0.5f * acc[2 * i + 1]));
            stsm_x4_trans(a, v[0], v[1], v[2], v[3]);
            stsm_x4_trans(a + 2048, v[4], v[5], v[6], v[7]);
            stsm_x2_trans(a + 4096, v[8], v[9]);
        }
        bar_sync(5 + wg, 128);
        {
            const int lim = min(min(N - cta * NPC, NPC) - half * 40, 40);
            __nv_bfloat16* op = out + (size_t)(cta * NPC + half * 40 + r8) * D + h * 64 + c8 * 8;
            uint4 v[3];
#pragma unroll
            for (int p = 0; p < 3; p++) v[p] = lds128(ot + r8 * 128 + ((c8 ^ (r8 & 7)) << 4) + p * 2048);
#pragma unroll
            for (int p = 0; p < 3; p++)
                if (r8 + 16 * p < lim) stg128(op + 16 * p * D, v[p]);
        }
        if (role == 3 && (tid & 127) == 0) STAMP(21);
    }
}

__global__ void fb_zero(int n) {
    for (int i = blockIdx.x * blockDim.x + threadIdx.x; i < n; i += gridDim.x * blockDim.x) g_aggf[i] = 0.f;
}
__global__ void fb_edge(const __nv_bfloat16* x, const __nv_bfloat16* e_attr, const int* src, const int* dst,
                        const __nv_bfloat16* w_msg, int E) {
    __shared__ float in[2 * D + DE];
    for (int e = blockIdx.x; e < E; e += gridDim.x) {
        int s = src[e], d = dst[e], c = threadIdx.x;
        __syncthreads();
        in[c] = __bfloat162float(x[(size_t)s * D + c]);
        in[D + c] = __bfloat162float(x[(size_t)d * D + c]);
        if (c < DE) in[2 * D + c] = __bfloat162float(e_attr[(size_t)e * DE + c]);
        __syncthreads();
        float a = 0.f;
        for (int k = 0; k < 2 * D + DE; k++) a = fmaf(in[k], __bfloat162float(w_msg[k * D + c]), a);
        atomicAdd(&g_aggf[(size_t)d * D + c], a / (1.f + __expf(-a)));
    }
}
__global__ void fb_node(const __nv_bfloat16* x, const __nv_bfloat16* w_upd, __nv_bfloat16* out, int N) {
    __shared__ float in[2 * D];
    for (int n = blockIdx.x; n < N; n += gridDim.x) {
        int c = threadIdx.x;
        __syncthreads();
        in[c] = __bfloat162float(x[(size_t)n * D + c]);
        in[D + c] = g_aggf[(size_t)n * D + c];
        __syncthreads();
        float a = 0.f;
        for (int k = 0; k < 2 * D; k++) a = fmaf(in[k], __bfloat162float(w_upd[k * D + c]), a);
        out[(size_t)n * D + c] = __float2bfloat16(a / (1.f + __expf(-a)));
    }
}

}

extern "C" void kernel_launch(void* const* d_in, const int* in_sizes, int n_in, void* d_out, int out_size) {
    const __nv_bfloat16* x = (const __nv_bfloat16*)d_in[0];
    const __nv_bfloat16* e_attr = (const __nv_bfloat16*)d_in[1];
    const int* src = (const int*)d_in[2];
    const int* dst = (const int*)d_in[3];
    const __nv_bfloat16* w_msg = (const __nv_bfloat16*)d_in[4];
    const __nv_bfloat16* w_upd = (const __nv_bfloat16*)d_in[5];
    __nv_bfloat16* out = (__nv_bfloat16*)d_out;
    const int N = in_sizes[0] / D, E = in_sizes[2];

    typedef CUresult (*EncodeFn)(CUtensorMap*, CUtensorMapDataType, cuuint32_t, void*, const cuuint64_t*, const cuuint64_t*,
                                 const cuuint32_t*, const cuuint32_t*, CUtensorMapInterleave, CUtensorMapSwizzle,
                                 CUtensorMapL2promotion, CUtensorMapFloatOOBfill);
    static int mode = -1;
    static void *pP = nullptr, *pSeg = nullptr, *pEp = nullptr;
    static EncodeFn encode = nullptr;
    if (mode < 0) {
        int dev = 0, sms = 0, nb = 0;
        cudaGetDevice(&dev);
        cudaDeviceGetAttribute(&sms, cudaDevAttrMultiProcessorCount, dev);
        cudaError_t e = cudaFuncSetAttribute(mpnn_kernel, cudaFuncAttributeMaxDynamicSharedMemorySize, SM_ALLOC);
        if (e == cudaSuccess) e = cudaOccupancyMaxActiveBlocksPerMultiprocessor(&nb, mpnn_kernel, NT, SM_ALLOC);
        if (e == cudaSuccess) e = cudaGetSymbolAddress(&pP, g_P);
        if (e == cudaSuccess) e = cudaGetSymbolAddress(&pSeg, g_seg);
        if (e == cudaSuccess) e = cudaGetSymbolAddress(&pEp, g_epoch);
        void* fn = nullptr;
        cudaDriverEntryPointQueryResult qr;
        if (e == cudaSuccess) e = cudaGetDriverEntryPoint("cuTensorMapEncodeTiled", &fn, cudaEnableDefault, &qr);
        encode = (EncodeFn)fn;
        mode = (e == cudaSuccess && nb >= 1 && sms >= G && encode != nullptr) ? 1 : 0;
        (void)cudaGetLastError();
    }
    bool fast = mode == 1 && N >= 1 && N <= NMAX && E <= EMAX && (E & 1) == 0;
    CUtensorMap tm[5];
    if (fast) {
        void* base[5] = {(void*)x, (void*)w_msg, (void*)w_upd, pP, (void*)out};
        const cuuint64_t rows[5] = {(cuuint64_t)N, 2 * D + DE, 2 * D, NMAX, (cuuint64_t)N};
        const cuuint32_t boxr[5] = {ROWS, 128, 128, NPC, NPC};
        for (int i = 0; i < 4 && fast; i++) {
            const cuuint64_t dims[2] = {D, rows[i]}, strides[1] = {D * 2};
            const cuuint32_t box[2] = {64, boxr[i]}, es[2] = {1, 1};
            fast = encode(&tm[i], CU_TENSOR_MAP_DATA_TYPE_BFLOAT16, 2, base[i], dims, strides, box, es, CU_TENSOR_MAP_INTERLEAVE_NONE,
                          CU_TENSOR_MAP_SWIZZLE_128B, CU_TENSOR_MAP_L2_PROMOTION_NONE, CU_TENSOR_MAP_FLOAT_OOB_FILL_NONE) == CUDA_SUCCESS;
        }
    }
    if (fast) {
        mpnn_kernel<<<G, NT, SM_ALLOC, cudaStreamPerThread>>>(e_attr, src, dst, w_msg, w_upd, out, (__nv_bfloat16*)pP, (uint32_t*)pSeg,
                                                              (unsigned long long*)pEp, N, E, tm[0], tm[1], tm[2], tm[3]);
    } else if ((long long)N * D <= 4 * 1024 * 1024) {
        fb_zero<<<256, 256, 0, cudaStreamPerThread>>>(N * D);
        fb_edge<<<2048, D, 0, cudaStreamPerThread>>>(x, e_attr, src, dst, w_msg, E);
        fb_node<<<2048, D, 0, cudaStreamPerThread>>>(x, w_upd, out, N);
    }
}
```

```cpp
#include <cuda.h>
#include <cuda_runtime.h>
#include <cuda_bf16.h>
#include <stdint.h>

namespace {

constexpr int D = 128;
constexpr int DE = 16;
constexpr int G = 132;
constexpr int NPC = 76;
constexpr int ROWS = 80;
constexpr int EPC = 1216;
constexpr int NT = 640;
constexpr int NMAX = G * NPC;
constexpr int EMAX = G * EPC;
constexpr int SEGCAP = 32;

constexpr int NTILE = 120;
constexpr int SM_XS = 0;
constexpr int SM_W = 20480;
constexpr int SM_AGG = SM_W + 65536;
constexpr int EAROWS = 1536;
constexpr int SM_EA = SM_AGG + 20480;
constexpr int SM_LIST = SM_EA + EAROWS * 32;
constexpr int TRASH = (NTILE + 4) * 16;
constexpr int SM_EL = SM_LIST + 8000;
constexpr int SM_EG = SM_EL + 8000;
constexpr int SM_W3F = SM_EG + 13312;
constexpr int SM_W3G = SM_W3F + 4096;
constexpr int SM_MISC = SM_W3G + 4096;
constexpr int SM_STG = SM_AGG;
constexpr int SM_TOTAL = SM_MISC + 3328;
constexpr int SM_ALLOC = SM_TOTAL + 1024;
constexpr int MI_SEG = 0;
constexpr int MI_SLOW = 544;
constexpr int MI_ECNT = 548;
constexpr int MI_TICKET = 552;
constexpr int MI_KEY = 560;
constexpr int MI_MB = 3264;
constexpr int MI_TAG = 1072;
constexpr int MI_PERM = 1088;
constexpr int MI_SKEY = 1408;
constexpr int MI_NREC = 1728;
constexpr int MI_ID = 2752;

constexpr uint32_t W_EMPTY = 0xFFFFFFFFu;
constexpr uint32_t T_EMPTY = 0x7FFFFFFFu;
constexpr uint32_t T_OVF = 0x7FFFBFFFu;
constexpr int GBLIND = 4;
constexpr int HSLACK = 66;
constexpr int SPIN_LIMIT = 1 << 20;

__device__ __align__(256) __nv_bfloat16 g_P[(NMAX + G) * D];
__device__ __align__(256) uint32_t g_seg[G * G * SEGCAP];
__device__ __align__(256) unsigned long long g_epoch[32];
__device__ float g_aggf[4 * 1024 * 1024];
#define STAMP(i) do { } while (0)

__device__ __forceinline__ uint32_t smem_u32(const void* p) { return (uint32_t)__cvta_generic_to_shared(p); }
__device__ __forceinline__ void fence_async() { asm volatile("fence.proxy.async.shared::cta;" ::: "memory"); }
__device__ __forceinline__ void bar_sync(int id, int n) { asm volatile("bar.sync %0, %1;" ::"r"(id), "r"(n) : "memory"); }
__device__ __forceinline__ void bar_arrive(int id, int n) { asm volatile("bar.arrive %0, %1;" ::"r"(id), "r"(n) : "memory"); }
__device__ __forceinline__ uint32_t lds32(uint32_t a) { uint32_t v; asm volatile("ld.shared.u32 %0, [%1];" : "=r"(v) : "r"(a) : "memory"); return v; }
__device__ __forceinline__ uint2 lds64(uint32_t a) { uint2 v; asm volatile("ld.shared.v2.u32 {%0,%1}, [%2];" : "=r"(v.x), "=r"(v.y) : "r"(a) : "memory"); return v; }
__device__ __forceinline__ uint4 lds128(uint32_t a) { uint4 v; asm volatile("ld.shared.v4.u32 {%0,%1,%2,%3}, [%4];" : "=r"(v.x), "=r"(v.y), "=r"(v.z), "=r"(v.w) : "r"(a) : "memory"); return v; }
__device__ __forceinline__ void sts32(uint32_t a, uint32_t v) { asm volatile("st.shared.u32 [%0], %1;" ::"r"(a), "r"(v) : "memory"); }
__device__ __forceinline__ void sts128(uint32_t a, uint4 v) { asm volatile("st.shared.v4.u32 [%0], {%1,%2,%3,%4};" ::"r"(a), "r"(v.x), "r"(v.y), "r"(v.z), "r"(v.w) : "memory"); }
__device__ __forceinline__ void sts32_lt(uint32_t a, uint32_t v, uint32_t x, uint32_t lim) {
    asm volatile("{\n.reg .pred p;\nsetp.lt.u32 p, %2, %3;\n@p st.shared.u32 [%0], %1;\n}" ::"r"(a), "r"(v), "r"(x), "r"(lim) : "memory");
}
__device__ __forceinline__ void sts64_lt(uint32_t a, uint32_t v, uint32_t w, uint32_t x, uint32_t lim) {
    asm volatile("{\n.reg .pred p;\nsetp.lt.u32 p, %3, %4;\n@p st.shared.v2.u32 [%0], {%1, %2};\n}" ::"r"(a), "r"(v), "r"(w), "r"(x), "r"(lim) : "memory");
}
__device__ __forceinline__ void cp_async16_lt(uint32_t dst, const void* src, int x, int lim) {
    asm volatile("{\n.reg .pred p;\nsetp.lt.s32 p, %2, %3;\n@p cp.async.cg.shared.global [%0], [%1], 16;\n}" ::"r"(dst), "l"(src), "r"(x), "r"(lim) : "memory");
}
__device__ __forceinline__ uint32_t atoms_add_lt(uint32_t a, int d, uint32_t x, uint32_t lim) {
    uint32_t v = 0;
    asm volatile("{\n.reg .pred p;\nsetp.lt.u32 p, %3, %4;\n@p atom.shared.add.u32 %0, [%1], %2;\n}" : "+r"(v) : "r"(a), "r"(d), "r"(x), "r"(lim) : "memory");
    return v;
}
__device__ __forceinline__ uint32_t atoms_add(uint32_t a, int d) { uint32_t v; asm volatile("atom.shared.add.u32 %0, [%1], %2;" : "=r"(v) : "r"(a), "r"(d) : "memory"); return v; }
__device__ __forceinline__ uint4 ldg128(const void* p) { uint4 v; asm volatile("ld.global.v4.u32 {%0,%1,%2,%3}, [%4];" : "=r"(v.x), "=r"(v.y), "=r"(v.z), "=r"(v.w) : "l"(p) : "memory"); return v; }
__device__ __forceinline__ uint2 ldg64(const void* p) { uint2 v; asm volatile("ld.global.v2.u32 {%0,%1}, [%2];" : "=r"(v.x), "=r"(v.y) : "l"(p) : "memory"); return v; }
__device__ __forceinline__ void sts64(uint32_t a, uint32_t x, uint32_t y) { asm volatile("st.shared.v2.u32 [%0], {%1,%2};" ::"r"(a), "r"(x), "r"(y) : "memory"); }
__device__ __forceinline__ void stg128(void* p, uint4 v) { asm volatile("st.global.v4.u32 [%0], {%1,%2,%3,%4};" ::"l"(p), "r"(v.x), "r"(v.y), "r"(v.z), "r"(v.w) : "memory"); }
__device__ __forceinline__ uint32_t pack_bf16(float lo, float hi) {
    uint32_t r; asm("cvt.rn.bf16x2.f32 %0, %1, %2;" : "=r"(r) : "f"(hi), "f"(lo)); return r;
}
__device__ __forceinline__ float tanh_fast(float x) { float r; asm("tanh.approx.f32 %0, %1;" : "=f"(r) : "f"(x)); return r; }
__device__ __forceinline__ float silu_half(float h) { return fmaf(h, tanh_fast(h), h); }
__device__ __forceinline__ uint32_t movm(uint32_t a) { uint32_t d; asm volatile("movmatrix.sync.aligned.m8n8.trans.b16 %0, %1;" : "=r"(d) : "r"(a)); return d; }
__device__ __forceinline__ uint32_t shl_clamp(uint32_t v, uint32_t s) { uint32_t d; asm("shl.b32 %0, %1, %2;" : "=r"(d) : "r"(v), "r"(s)); return d; }
__device__ __forceinline__ void mma16(float (&d)[4], uint32_t a0, uint32_t a1, uint32_t a2, uint32_t a3, uint32_t b0, uint32_t b1) {
    asm("mma.sync.aligned.m16n8k16.row.col.f32.bf16.bf16.f32 {%0,%1,%2,%3}, {%4,%5,%6,%7}, {%8,%9}, {%0,%1,%2,%3};"
        : "+f"(d[0]), "+f"(d[1]), "+f"(d[2]), "+f"(d[3]) : "r"(a0), "r"(a1), "r"(a2), "r"(a3), "r"(b0), "r"(b1));
}
__device__ __forceinline__ void mma16_c(float (&d)[4], uint32_t a0, uint32_t a1, uint32_t a2, uint32_t a3, uint32_t b0, uint32_t b1, const float (&c)[4]) {
    asm("mma.sync.aligned.m16n8k16.row.col.f32.bf16.bf16.f32 {%0,%1,%2,%3}, {%4,%5,%6,%7}, {%8,%9}, {%10,%11,%12,%13};"
        : "=f"(d[0]), "=f"(d[1]), "=f"(d[2]), "=f"(d[3]) : "r"(a0), "r"(a1), "r"(a2), "r"(a3), "r"(b0), "r"(b1),
          "f"(c[0]), "f"(c[1]), "f"(c[2]), "f"(c[3]));
}
__device__ __forceinline__ void stsm_x4_trans(uint32_t addr, uint32_t r0, uint32_t r1, uint32_t r2, uint32_t r3) {
    asm volatile("stmatrix.sync.aligned.m8n8.x4.trans.shared.b16 [%0], {%1,%2,%3,%4};" ::"r"(addr), "r"(r0), "r"(r1), "r"(r2), "r"(r3) : "memory");
}

__device__ __forceinline__ uint64_t make_desc(uint32_t addr) {
    return (uint64_t)((addr & 0x3FFFF) >> 4) | ((uint64_t)64 << 16) | ((uint64_t)64 << 32) | ((uint64_t)1 << 62);
}
__device__ __forceinline__ void wg_fence() { asm volatile("wgmma.fence.sync.aligned;" ::: "memory"); }
__device__ __forceinline__ void wg_commit() { asm volatile("wgmma.commit_group.sync.aligned;" ::: "memory"); }
template <int N> __device__ __forceinline__ void wg_wait() { asm volatile("wgmma.wait_group.sync.aligned %0;" ::"n"(N) : "memory"); }
__device__ __forceinline__ void wgmma_n80(float (&d)[40], uint64_t da, uint64_t db, int scale_d) {
    asm volatile(
        "{\n.reg .pred p;\nsetp.ne.b32 p, %42, 0;\n"
        "wgmma.mma_async.sync.aligned.m64n80k16.f32.bf16.bf16 "
        "{%0,%1,%2,%3,%4,%5,%6,%7,%8,%9,%10,%11,%12,%13,%14,%15,%16,%17,%18,%19,"
        "%20,%21,%22,%23,%24,%25,%26,%27,%28,%29,%30,%31,%32,%33,%34,%35,%36,%37,%38,%39}, "
        "%40, %41, p, 1, 1, 1, 0;\n}\n"
        : "+f"(d[0]), "+f"(d[1]), "+f"(d[2]), "+f"(d[3]), "+f"(d[4]), "+f"(d[5]), "+f"(d[6]), "+f"(d[7]), "+f"(d[8]), "+f"(d[9]),
          "+f"(d[10]), "+f"(d[11]), "+f"(d[12]), "+f"(d[13]), "+f"(d[14]), "+f"(d[15]), "+f"(d[16]), "+f"(d[17]), "+f"(d[18]), "+f"(d[19]),
          "+f"(d[20]), "+f"(d[21]), "+f"(d[22]), "+f"(d[23]), "+f"(d[24]), "+f"(d[25]), "+f"(d[26]), "+f"(d[27]), "+f"(d[28]), "+f"(d[29]),
          "+f"(d[30]), "+f"(d[31]), "+f"(d[32]), "+f"(d[33]), "+f"(d[34]), "+f"(d[35]), "+f"(d[36]), "+f"(d[37]), "+f"(d[38]), "+f"(d[39])
        : "l"(da), "l"(db), "r"(scale_d));
}

__device__ __forceinline__ void wgmma_n40(float (&d)[20], uint64_t da, uint64_t db, int scale_d) {
    asm volatile(
        "{\n.reg .pred p;\nsetp.ne.b32 p, %22, 0;\n"
        "wgmma.mma_async.sync.aligned.m64n40k16.f32.bf16.bf16 "
        "{%0,%1,%2,%3,%4,%5,%6,%7,%8,%9,%10,%11,%12,%13,%14,%15,%16,%17,%18,%19}, "
        "%20, %21, p, 1, 1, 1, 0;\n}\n"
        : "+f"(d[0]), "+f"(d[1]), "+f"(d[2]), "+f"(d[3]), "+f"(d[4]), "+f"(d[5]), "+f"(d[6]), "+f"(d[7]), "+f"(d[8]), "+f"(d[9]),
          "+f"(d[10]), "+f"(d[11]), "+f"(d[12]), "+f"(d[13]), "+f"(d[14]), "+f"(d[15]), "+f"(d[16]), "+f"(d[17]), "+f"(d[18]), "+f"(d[19])
        : "l"(da), "l"(db), "r"(scale_d));
}
__device__ __forceinline__ void stsm_x2_trans(uint32_t addr, uint32_t r0, uint32_t r1) {
    asm volatile("stmatrix.sync.aligned.m8n8.x2.trans.shared.b16 [%0], {%1,%2};" ::"r"(addr), "r"(r0), "r"(r1) : "memory");
}
__device__ __forceinline__ uint4 ldg128_rlx(const void* p) { uint4 v; asm volatile("ld.relaxed.gpu.global.v4.u32 {%0,%1,%2,%3}, [%4];" : "=r"(v.x), "=r"(v.y), "=r"(v.z), "=r"(v.w) : "l"(p) : "memory"); return v; }
__device__ __forceinline__ void stg128_rlx(void* p, uint4 v) { asm volatile("st.relaxed.gpu.global.v4.u32 [%0], {%1,%2,%3,%4};" ::"l"(p), "r"(v.x), "r"(v.y), "r"(v.z), "r"(v.w) : "memory"); }

__device__ __forceinline__ unsigned long long ldg64_rlx(const void* p) { unsigned long long v; asm volatile("ld.relaxed.gpu.global.u64 %0, [%1];" : "=l"(v) : "l"(p) : "memory"); return v; }
__device__ __forceinline__ void hint_arrive(unsigned long long* p) { asm volatile("red.relaxed.gpu.global.add.u64 [%0], 1;" ::"l"(p) : "memory"); }
__device__ __forceinline__ void hint_wait(const unsigned long long* p, unsigned long long target) {
#pragma unroll 1
    for (int it = 0; it < SPIN_LIMIT; it++)
        if (ldg64_rlx(p) >= target) break;
}

__host__ __device__ constexpr int boundary(int k) { return k == 0 ? 8 : 24 + 21 * k; }
__device__ __forceinline__ uint32_t tile_addr(uint32_t base, int row, int c) {
    return base + (c >> 3) * 10240 + row * 128 + (((c & 7) ^ (row & 7)) << 4);
}

__device__ __forceinline__ uint32_t split_cap(uint32_t sm) {
    const int d0 = lds32(sm + MI_SKEY) >> 7, d4 = lds32(sm + MI_SKEY + 16) >> 7, d72 = lds32(sm + MI_SKEY + 288) >> 7;
    return max(d4, d0 - ((d72 + 1) & ~1));
}

struct Tile { uint4 p0, p1; };
struct Consts { uint4 w3[2]; uint4 id; uint32_t par, q8; const unsigned char* pb; };

__device__ __forceinline__ void fetch(Tile& st, uint32_t la, const Consts& k) {
    uint2 e = lds64(la);
    st.p0 = ldg128_rlx(k.pb + (size_t)e.x * 256);
    st.p1 = ldg128_rlx(k.pb + (size_t)e.y * 256);
}
__device__ __forceinline__ bool stale(const Tile& a, const Tile& b, const Consts& k) {
    uint32_t t, u;
    asm("lop3.b32 %0, %1, %2, %3, 0x7E;" : "=r"(t) : "r"(a.p0.x), "r"(a.p1.x), "r"(k.par));
    asm("lop3.b32 %0, %1, %2, %3, 0x7E;" : "=r"(u) : "r"(b.p0.x), "r"(b.p1.x), "r"(k.par));
    asm("lop3.b32 %0, %1, %2, 1, 0xA8;" : "=r"(t) : "r"(t), "r"(u));
    return __any_sync(0xffffffffu, t != 0);
}
__device__ __forceinline__ void validate(Tile& a, Tile& b, uint32_t la, const Consts& k) {
    if (__builtin_expect(stale(a, b, k), 0)) {
#pragma unroll 1
        for (int it = 0; it < SPIN_LIMIT; it++) {
            fetch(a, la, k);
            fetch(b, la + 64, k);
            if (!stale(a, b, k)) break;
        }
    }
}
__device__ __forceinline__ void tile_mma(float (&acc)[2][4], const Tile& st, uint2 eo, const float (&qi)[2][4], const Consts& k) {
    const uint2 ea0 = lds64(eo.x | k.q8), ea1 = lds64(eo.y | k.q8);
    float c[2][2][4];
#pragma unroll
    for (int u = 0; u < 2; u++) {
        mma16_c(c[u][0], k.id.x, k.id.y, k.id.z, k.id.w, u ? st.p0.z : st.p0.x, u ? st.p0.w : st.p0.y, qi[u]);
        mma16_c(c[u][1], k.id.x, k.id.y, k.id.z, k.id.w, u ? st.p1.z : st.p1.x, u ? st.p1.w : st.p1.y, qi[u]);
    }
#pragma unroll
    for (int u = 0; u < 2; u++) {
        mma16(c[u][0], k.w3[u].x, k.w3[u].y, k.w3[u].z, k.w3[u].w, ea0.x, ea0.y);
        mma16(c[u][1], k.w3[u].x, k.w3[u].y, k.w3[u].z, k.w3[u].w, ea1.x, ea1.y);
    }
#pragma unroll
    for (int u = 0; u < 2; u++)
#pragma unroll
        for (int n = 0; n < 2; n++)
#pragma unroll
            for (int i = 0; i < 4; i++) acc[u][i] += silu_half(c[u][n][i]);
}
__device__ __forceinline__ void load_q(float (&qi)[2][4], uint32_t sb, int ra, int rb, int f, int g) {
    const uint4 a = lds128(tile_addr(sb + SM_AGG, ra, 4 * f + (g >> 1))), b = lds128(tile_addr(sb + SM_AGG, rb, 4 * f + (g >> 1)));
    const uint32_t sel = (g & 1) ? 0x3244u : 0x1044u;
    qi[0][0] = 0.5f * __uint_as_float(__byte_perm(a.x, 0, sel)); qi[0][1] = 0.5f * __uint_as_float(__byte_perm(b.x, 0, sel));
    qi[0][2] = 0.5f * __uint_as_float(__byte_perm(a.y, 0, sel)); qi[0][3] = 0.5f * __uint_as_float(__byte_perm(b.y, 0, sel));
    qi[1][0] = 0.5f * __uint_as_float(__byte_perm(a.z, 0, sel)); qi[1][1] = 0.5f * __uint_as_float(__byte_perm(b.z, 0, sel));
    qi[1][2] = 0.5f * __uint_as_float(__byte_perm(a.w, 0, sel)); qi[1][3] = 0.5f * __uint_as_float(__byte_perm(b.w, 0, sel));
}
__device__ __forceinline__ void flush_agg(uint32_t addr, const float (&acc)[2][4]) {
    uint4 v;
    v.x = movm(pack_bf16(acc[0][0], acc[0][1]));
    v.y = movm(pack_bf16(acc[0][2], acc[0][3]));
    v.z = movm(pack_bf16(acc[1][0], acc[1][1]));
    v.w = movm(pack_bf16(acc[1][2], acc[1][3]));
    sts128(addr, v);
}

__device__ __forceinline__ void tma_load(uint32_t dst, const CUtensorMap* tm, int c0, int c1, uint32_t mbar) {
    asm volatile("cp.async.bulk.tensor.2d.shared::cluster.global.mbarrier::complete_tx::bytes [%0], [%1, {%2, %3}], [%4];"
                 ::"r"(dst), "l"(tm), "r"(c0), "r"(c1), "r"(mbar) : "memory");
}
__device__ __forceinline__ void tma_store(const CUtensorMap* tm, int c0, int c1, uint32_t src) {
    asm volatile("cp.async.bulk.tensor.2d.global.shared::cta.bulk_group [%0, {%1, %2}], [%3];" ::"l"(tm), "r"(c0), "r"(c1), "r"(src) : "memory");
    asm volatile("cp.async.bulk.commit_group;" ::: "memory");
}
__device__ __forceinline__ void tma_store_wait() { asm volatile("cp.async.bulk.wait_group.read 0;" ::: "memory"); }
__device__ __forceinline__ void mbar_wait0(uint32_t a) {
    for (int it = 0; it < SPIN_LIMIT; it++) {
        uint32_t ok;
        asm volatile("{\n.reg .pred p;\nmbarrier.try_wait.parity.shared::cta.b64 p, [%1], 0;\nselp.u32 %0, 1, 0, p;\n}" : "=r"(ok) : "r"(a) : "memory");
        if (ok) break;
    }
}

__device__ __noinline__ void slow_path(uint32_t sb, const __nv_bfloat16* e_attr, const int* src, const int* dst, int E, Consts k) {
    const int tid = threadIdx.x, lane = tid & 31, wg = tid >> 7, f = (tid >> 5) & 3, g = lane >> 2, q = lane & 3, cta = blockIdx.x;
    const uint32_t s_deg = sb + SM_MISC + MI_KEY;
    float acc[2][2][4];
    for (int i = 0; i < 16; i++) (&acc[0][0][0])[i] = 0.f;
    int scan = 0, state = 0, row = 0;
    bool more = true;
    while (more) {
        more = false;
        __syncthreads();
        if (tid < ROWS) sts32(s_deg + tid * 4, 0);
        for (int i = tid; i < EAROWS * 2; i += NT) sts128(sb + SM_EA + i * 16, make_uint4(0, 0, 0, 0));
        for (int i = tid; i < (NTILE + 4) * 16; i += NT) sts32(sb + SM_LIST + i * 4, NMAX + cta);
        __syncthreads();
        while (true) {
            const int e = scan + tid;
            if (state == 0) {
                state = 2;
                if (e < E) {
                    int dn = dst[e];
                    if (dn / NPC == cta) { state = 1; row = dn - cta * NPC; }
                }
            }
            if (state == 1) {
                uint32_t rank = atoms_add(s_deg + row * 4, 1);
                if (rank < 18) {
                    uint32_t pos = ((row >> 3) * 9 + (rank >> 1)) * 16 + (row & 7) * 2 + (rank & 1);
                    sts32(sb + SM_LIST + pos * 4, (uint32_t)src[e]);
                    sts128(sb + SM_EA + pos * 32, ldg128(e_attr + (size_t)e * DE));
                    sts128(sb + SM_EA + pos * 32 + 16, ldg128(e_attr + (size_t)e * DE + 8));
                    state = 2;
                }
            }
            if (__syncthreads_or(state == 1)) { more = true; break; }
            scan += NT;
            state = 0;
            if (scan >= E) break;
        }
#pragma unroll
        for (int b = 0; b < 2; b++) {
            const int grp = 2 * wg + b;
            const int mx = min((int)__reduce_max_sync(0xffffffffu, lds32(s_deg + (grp * 8 + g) * 4)), 18);
            float qi[2][4];
            load_q(qi, sb, grp * 8 + 2 * q, grp * 8 + 2 * q + 1, f, g);
            for (int t = 0; t * 2 < mx; t++) {
                const int tile = grp * 9 + t;
                Tile st, s2;
                const uint32_t la = sb + SM_LIST + tile * 64 + g * 8;
                fetch(st, la, k);
                fetch(s2, la + 64, k);
                validate(st, s2, la, k);
                tile_mma(acc[b], st, make_uint2(sb + SM_EA + tile * 512 + g * 64, sb + SM_EA + tile * 512 + g * 64 + 32), qi, k);
            }
        }
    }
    __syncwarp();
    flush_agg(tile_addr(sb + SM_AGG, wg * 16 + g, 4 * f + q), acc[0]);
    flush_agg(tile_addr(sb + SM_AGG, wg * 16 + 8 + g, 4 * f + q), acc[1]);
}

__global__ void __launch_bounds__(NT, 1)
mpnn_kernel(const __nv_bfloat16* __restrict__ e_attr, const int* __restrict__ src, const int* __restrict__ dst,
            const __nv_bfloat16* __restrict__ w_msg, const __nv_bfloat16* __restrict__ w_upd,
            __nv_bfloat16* __restrict__ out, __nv_bfloat16* __restrict__ gP, uint32_t* __restrict__ gseg,
            unsigned long long* __restrict__ gepoch, int N, int E,
            const __grid_constant__ CUtensorMap tm_x, const __grid_constant__ CUtensorMap tm_wm,
            const __grid_constant__ CUtensorMap tm_wu, const __grid_constant__ CUtensorMap tm_p) {
    extern __shared__ unsigned char smem_raw[];
    const uint32_t sb = (smem_u32(smem_raw) + 1023u) & ~1023u;
    const int tid = threadIdx.x, warp = tid >> 5, lane = tid & 31;
    const int wg = warp >> 2, f = warp & 3, g = lane >> 2, q = lane & 3;
    const int cta = blockIdx.x;
    const int wgu = (int)__reduce_max_sync(0xffffffffu, (uint32_t)wg);
    const uint32_t sm = sb + SM_MISC;
    if (tid == 0) STAMP(0);

    uint2 d2 = make_uint2(~0u, 0), s2;
    {
        const int e0 = ((tid >> 4) * G + cta) * 32 + (tid & 15) * 2;
        if (tid < EPC / 2 && e0 < E) {
            d2 = ldg64(dst + e0);
            s2 = ldg64(src + e0);
        }
    }
    unsigned long long cnt0 = 0;
    if (tid == 576) cnt0 = ldg64_rlx(gepoch);
    sts128(sb + SM_STG + tid * 16, make_uint4(W_EMPTY, W_EMPTY, W_EMPTY, W_EMPTY));
    if (tid < 416) sts128(sb + SM_STG + 10240 + tid * 16, make_uint4(W_EMPTY, W_EMPTY, W_EMPTY, W_EMPTY));
    else if (tid < 636) sts32(sm + (tid - 416) * 4, tid >= 556 ? 127 - (tid - 556) : tid == 553);
    if (warp == 19) {
        if (lane == 31) {
            asm volatile("mbarrier.init.shared::cta.b64 [%0], 1;" ::"r"(sm + MI_MB) : "memory");
            asm volatile("mbarrier.init.shared::cta.b64 [%0], 1;" ::"r"(sm + MI_MB + 8) : "memory");
            asm volatile("mbarrier.init.shared::cta.b64 [%0], 96;" ::"r"(sm + MI_MB + 16) : "memory");
            asm volatile("mbarrier.init.shared::cta.b64 [%0], 96;" ::"r"(sm + MI_MB + 24) : "memory");
            asm volatile("mbarrier.init.shared::cta.b64 [%0], 20;" ::"r"(sm + MI_MB + 32) : "memory");
            sts64(sm + MI_NREC + 127 * 8, 0x40000000u, 0u);
        }
        __syncwarp();
        bar_arrive(3, 640);
        if (lane == 31) {
            fence_async();
            asm volatile("mbarrier.arrive.expect_tx.shared::cta.b64 _, [%0], %1;" ::"r"(sm + MI_MB), "r"(20480 + 65536 + 4096) : "memory");
            asm volatile("mbarrier.arrive.expect_tx.shared::cta.b64 _, [%0], %1;" ::"r"(sm + MI_MB + 8), "r"(65536) : "memory");
#pragma unroll
            for (int b = 0; b < 4; b++) tma_load(sb + SM_W + b * 16384, &tm_wm, (b & 1) * 64, (b >> 1) * 128, sm + MI_MB);
            asm volatile("cp.async.bulk.shared::cluster.global.mbarrier::complete_tx::bytes [%0], [%1], 4096, [%2];"
                         ::"r"(sb + SM_W3F), "l"(w_msg + 2 * D * D), "r"(sm + MI_MB) : "memory");
            tma_load(sb + SM_XS, &tm_x, 0, cta * NPC, sm + MI_MB);
            tma_load(sb + SM_XS + 10240, &tm_x, 64, cta * NPC, sm + MI_MB);
            asm volatile("prefetch.tensormap [%0];" ::"l"(&tm_p) : "memory");
            asm volatile("prefetch.tensormap [%0];" ::"l"(&tm_wu) : "memory");
        }
        __syncwarp();
    } else {
        bar_sync(3, 640);
    }
    if (tid == 0) STAMP(23);
    if (tid >= 636)
        asm volatile("prefetch.global.L2 [%0];" ::"l"(reinterpret_cast<const unsigned char*>(w_upd) + min(cta * 4 + (tid - 636), 511) * 128));
    if (d2.x != ~0u) {
        const uint32_t dc0 = d2.x / NPC, dc1 = d2.y / NPC;
        const uint32_t r0 = atoms_add(sm + MI_SEG + dc0 * 4, 1), r1 = atoms_add(sm + MI_SEG + dc1 * 4, 1);
        const uint32_t w0 = s2.x | (((tid << 8) + d2.x - dc0 * NPC) << 14), w1 = s2.y | (((tid << 8) + 128 + d2.y - dc1 * NPC) << 14);
        sts32_lt(sb + SM_STG + dc0 * 128 + (r0 & 7) * 16 + (r0 >> 3) * 4, w0, r0, SEGCAP);
        sts32_lt(sb + SM_STG + dc1 * 128 + (r1 & 7) * 16 + (r1 >> 3) * 4, w1, r1, SEGCAP);
    }
    if (tid == 576) {
        cnt0 = cnt0 / G + 1;
        sts64(sm + MI_TAG, (uint32_t)cnt0, (uint32_t)(cnt0 >> 32));
    }
    if (tid == 0) STAMP(24);
    __syncthreads();
    const uint32_t tag = lds32(sm + MI_TAG);
    const uint32_t parw = tag << 31;
    {
        uint4 v[2];
        uint32_t cn[2];
#pragma unroll
        for (int i = 0; i < 2; i++) {
            v[i] = lds128(sb + SM_STG + tid * 16 + i * 10240);
            cn[i] = lds32(sm + MI_SEG + min((tid >> 3) + i * 80, 135) * 4);
        }
#pragma unroll
        for (int i = 0; i < 2; i++) {
            uint32_t tl = T_EMPTY;
            if (cn[i] > 24) {
                const uint32_t w = v[i].w;
                if (w != W_EMPTY) tl = (((w >> 21) * ROWS + ((w >> 14) & 127u)) << 14) | (w & 16383u);
                if (cn[i] > SEGCAP) tl = T_OVF;
            }
            v[i].w = tl | parw;
            if (i == 0 || tid < 416) stg128_rlx(gseg + (size_t)cta * (G * SEGCAP) + tid * 4 + i * 2560, v[i]);
        }
    }
    const uint32_t* bp = gseg + ((size_t)(tid >> 3) * G + cta) * SEGCAP + (tid & 7) * 4;
    uint4 v1 = make_uint4(W_EMPTY, W_EMPTY, W_EMPTY, T_EMPTY | parw), v0 = v1;
    auto prefill2 = [&]() {
        const uint32_t pr = NMAX + cta;
        if (tid < 496) sts128(sb + SM_LIST + tid * 16, make_uint4(pr, pr, pr, pr));
        if (tid >= 144) sts128(sb + SM_EL + (tid - 144) * 16, make_uint4(sb + SM_EA, sb + SM_EA, sb + SM_EA, sb + SM_EA));
        else if (tid >= 142) sts128(sb + SM_EA + (tid - 142) * 16, make_uint4(0, 0, 0, 0));
        else if (tid < 32) {
            uint32_t idf = shl_clamp(0x3F00u, (uint32_t)((g - 2 * q) << 4));
            sts128(sm + MI_ID + lane * 16, make_uint4(idf, 0, 0, idf));
        }
    };
    const uint32_t so = (((lane >> 4) & 1) * 8 + (lane & 7)) * 128 + (((f * 2 + ((lane >> 3) & 1)) ^ (lane & 7)) << 4);
    if (wgu < 2) {
        bar_arrive(2, 640);
        prefill2();
        mbar_wait0(sm + MI_MB);
        if (tid == 0) STAMP(1);
        if (tid == 255) {
            int eb = cta * EPC, ne = min(EPC, E - eb);
            if (ne > 0) asm volatile("cp.async.bulk.prefetch.L2.global [%0], %1;" ::"l"(e_attr + (size_t)eb * DE), "r"(ne * 32) : "memory");
        }
        float gacc[40];
        const uint64_t da = make_desc(sb + SM_W + wgu * 16384), db = make_desc(sb + SM_XS);
        wg_fence();
#pragma unroll
        for (int ks = 0; ks < 8; ks++) wgmma_n80(gacc, da + ks * 128, db + (ks >> 2) * 640 + (ks & 3) * 2, ks);
        wg_commit();
        const uint32_t keep = g == 0 ? 0xFFFEFFFEu : 0xFFFFFFFFu, setb = g == 0 ? (tag & 1u) * 0x10001u : 0u;
        wg_wait<0>();
        if (tid == 0) STAMP(2);
        bar_sync(7 + wg, 128);
#pragma unroll
        for (int j = 0; j < 5; j++)
            stsm_x4_trans(sb + SM_W + wg * 16384 + so + j * 2048,
                          (pack_bf16(gacc[8 * j], gacc[8 * j + 1]) & keep) | setb, (pack_bf16(gacc[8 * j + 2], gacc[8 * j + 3]) & keep) | setb,
                          (pack_bf16(gacc[8 * j + 4], gacc[8 * j + 5]) & keep) | setb, (pack_bf16(gacc[8 * j + 6], gacc[8 * j + 7]) & keep) | setb);
        fence_async();
        bar_arrive(5, 288);
        bar_sync(12, 288);
        if (tid == 0) STAMP(22);
        v0 = ldg128_rlx(bp);
        v1 = ldg128_rlx(bp + (size_t)68 * G * SEGCAP);
    } else if (wgu < 4) {
        bar_arrive(2, 640);
        prefill2();
        bar_sync(4, 384);
        v0 = ldg128_rlx(bp);
        v1 = ldg128_rlx(bp + (size_t)68 * G * SEGCAP);
        float gacc[40];
        const uint64_t da = make_desc(sb + SM_W + wgu * 16384), db = make_desc(sb + SM_XS);
        mbar_wait0(sm + MI_MB);
        __syncwarp();
        wg_fence();
#pragma unroll
        for (int ks = 0; ks < 8; ks++) wgmma_n80(gacc, da + ks * 128, db + (ks >> 2) * 640 + (ks & 3) * 2, ks);
        wg_commit();
        wg_wait<0>();
#pragma unroll
        for (int j = 0; j < 5; j++)
            stsm_x4_trans(sb + SM_AGG + (wg - 2) * 10240 + so + j * 2048,
                          pack_bf16(gacc[8 * j], gacc[8 * j + 1]), pack_bf16(gacc[8 * j + 2], gacc[8 * j + 3]),
                          pack_bf16(gacc[8 * j + 4], gacc[8 * j + 5]), pack_bf16(gacc[8 * j + 6], gacc[8 * j + 7]));
    } else {
        if (warp < 19) bar_arrive(2, 640);
        prefill2();
        if (tid >= 624)
            stg128_rlx(gP + (size_t)(NMAX + cta) * D + (tid - 624) * 8, make_uint4(0xFF00FF00u | (tag & 1u), 0xFF00FF00u, 0xFF00FF00u, 0xFF00FF00u));
        if (warp == 19) {
            bar_sync(2, 640);
            if (lane == 0) { STAMP(4); hint_arrive(gepoch); hint_wait(gepoch, (((unsigned long long)lds32(sm + MI_TAG + 4) << 32) | tag) * G - HSLACK); STAMP(7); }
            __syncwarp();
            bar_arrive(12, 288);
        } else {
            mbar_wait0(sm + MI_MB);
#pragma unroll 1
            for (int ff = f; ff < 4; ff += 3) {
                const uint32_t wa = sb + SM_W3F + (4 * q * D + 32 * ff + (g >> 1) * 8 + (g & 1)) * 2;
                uint32_t w[8];
#pragma unroll
                for (int i = 0; i < 8; i++) {
                    const int u = i >> 2, r = i & 3, o = 4 * u + 2 * (r & 1) + 2 * (r >> 1) * D;
                    unsigned short lo, hi;
                    asm volatile("ld.shared.u16 %0, [%1];" : "=h"(lo) : "r"(wa + o * 2));
                    asm volatile("ld.shared.u16 %0, [%1];" : "=h"(hi) : "r"(wa + (o + D) * 2));
                    asm("mul.bf16x2 %0, %1, %2;" : "=r"(w[i]) : "r"((uint32_t)lo | ((uint32_t)hi << 16)), "r"(0x3F003F00u));
                }
                sts128(sb + SM_W3G + ff * 1024 + lane * 16, make_uint4(w[0], w[1], w[2], w[3]));
                sts128(sb + SM_W3G + ff * 1024 + 512 + lane * 16, make_uint4(w[4], w[5], w[6], w[7]));
            }
        }
        bar_sync(4, 384);
        if (warp == 16) v0 = ldg128_rlx(bp);
    }
    if (warp >= 17) {
        if (warp == 17) {
            bar_sync(5, 288);
            if (lane == 0) {
                tma_store(&tm_p, 0, cta * NPC, sb + SM_W);
                tma_store(&tm_p, 64, cta * NPC, sb + SM_W + 16384);
                STAMP(3);
            }
            __syncwarp();
        }
        bar_sync(6, 640);
        const int n = min((int)lds32(sm + MI_ECNT), EAROWS);
        const unsigned char* geb = reinterpret_cast<const unsigned char*>(e_attr) + (lane & 1) * 16;
        const int n0 = lds32(sm + MI_SLOW) == 0 ? n : 0;
        const int r0 = 1 + (lane >> 1) + (warp - 17) * 32;
#pragma unroll
        for (int it = 0; it < GBLIND; it++)
#pragma unroll
            for (int j = 0; j < 2; j++) {
                const int r = r0 + it * 96 + j * 16;
                cp_async16_lt(sb + SM_EA + r * 32 + (lane & 1) * 16, geb + lds32(sb + SM_EG + r * 8), r, n0);
            }
        constexpr int GR = 28 - 2 * GBLIND;
        uint2 rc[GR];
#pragma unroll
        for (int j = 0; j < GR; j++) rc[j] = lds64(sb + SM_EG + (r0 + (GBLIND + (j >> 1)) * 96 + (j & 1) * 16) * 8);
#pragma unroll 1
        for (int r = r0 + (GBLIND + GR / 2) * 96; r < n0 + 16; r += 96) {
            cp_async16_lt(sb + SM_EA + r * 32 + (lane & 1) * 16, geb + lds32(sb + SM_EG + r * 8), r, n0);
            cp_async16_lt(sb + SM_EA + r * 32 + 512 + (lane & 1) * 16, geb + lds32(sb + SM_EG + r * 8 + 128), r + 16, n0);
        }
        bar_sync(10, 640);
#pragma unroll
        for (int j = 0; j < GR; j++) rc[j].y = lds32(sm + MI_NREC + 4 + ((rc[j].y >> 11) & 1016u));
#pragma unroll
        for (int ph = 0; ph < 2; ph++) {
#pragma unroll
            for (int j = 0; j < GR; j++) {
                const int r = r0 + (GBLIND + (j >> 1)) * 96 + (j & 1) * 16;
                cp_async16_lt(sb + SM_EA + r * 32 + (lane & 1) * 16, geb + rc[j].x, ((rc[j].y != 0u) == (ph == 0)) ? r : n0, n0);
            }
            asm volatile("cp.async.mbarrier.arrive.noinc.shared::cta.b64 [%0];" ::"r"(sm + MI_MB + 24 - ph * 8) : "memory");
            if (ph == 0 && tid == 544) STAMP(10);
        }
        if (tid == 544) STAMP(12);
        bar_sync(11, 640);
    } else {
        __syncwarp();
#pragma unroll 1
        for (int it = 0; it < SPIN_LIMIT; it++) {
            if (!__any_sync(0xffffffffu, (int)((v0.w ^ parw) | (v1.w ^ parw)) < 0)) break;
            if (it) __nanosleep(200);
            v0 = ldg128_rlx(bp);
            if (wg < 4) v1 = ldg128_rlx(bp + (size_t)68 * G * SEGCAP);
        }
        if (tid == 0) STAMP(8);
        const uint32_t lt = (1u << lane) - 1u;
        uint32_t en[8] = {v0.x, v1.x, v0.y, v1.y, v0.z, v1.z, W_EMPTY, W_EMPTY}, es[8], gb = 0;
        int gt = 0;
        auto count = [&](int i) {
            const uint32_t m = __ballot_sync(0xffffffffu, en[i] != W_EMPTY);
            es[i] = gt + __popc(m & lt);
            gt += __popc(m);
        };
        auto put = [&](int i) {
            const uint32_t el = en[i] >> 21;
            sts64_lt(sb + SM_EG + (gb + es[i]) * 8, (el + (el >> 5) * (G * 32 - 32) + ((tid >> 3) + (i & 1) * 68) * 32) * 32, en[i], en[i], W_EMPTY);
        };
#pragma unroll
        for (int i = 0; i < 6; i++) count(i);
        const bool deep = __any_sync(0xffffffffu, (v0.w & v1.w & T_EMPTY) != T_EMPTY);
        if (deep) {
#pragma unroll
            for (int r = 0; r < 2; r++) {
                const uint32_t tl = (r ? v1.w : v0.w) & T_EMPTY, er = tl >> 14, el = ((er >> 4) * 52429u) >> 18;
                if (tl == T_OVF) sts32(sm + MI_SLOW, 1);
                if (tl < T_OVF) en[6 + r] = (el << 21) | ((er - el * ROWS) << 14) | (tl & 16383u);
                count(6 + r);
            }
        }
        if (lane == 0) gb = atoms_add(sm + MI_ECNT, gt);
        gb = __shfl_sync(0xffffffffu, gb, 0);
        if (gb + gt > EAROWS || gt > 128) { sts32(sm + MI_SLOW, 1); gb = 0; gt = 0; }
#pragma unroll
        for (int i = 0; i < 6; i++) put(i);
        if (deep) { put(6); put(7); }
        __syncwarp();
        bar_arrive(6, 640);
        uint32_t rec[4], rk[4];
#pragma unroll
        for (int j = 0; j < 4; j++) rec[j] = lds32(sb + SM_EG + (gb + lane) * 8 + 4 + j * 256);
#pragma unroll
        for (int j = 0; j < 4; j++) {
            if (lane + 32 * j >= gt) rec[j] = W_EMPTY;
            rk[j] = 0;
            if (32 * j < gt) rk[j] = atoms_add_lt(sm + MI_KEY + ((rec[j] >> 12) & 508u), 128, rec[j], W_EMPTY);
        }
        bar_sync(9, 544);
        if (tid == 0) STAMP(9);
        if (warp < 10) {
            const uint32_t key = lds32(sm + MI_KEY + (tid >> 2) * 4);
            uint4 o[5];
#pragma unroll
            for (int i = 0; i < 5; i++) o[i] = lds128(sm + MI_KEY + (tid & 3) * 80 + i * 16);
            uint32_t sp = 0, sq = 0;
#pragma unroll
            for (int i = 0; i < 5; i++) {
                sp += (key - o[i].x) >> 31; sq += (key - o[i].y) >> 31;
                sp += (key - o[i].z) >> 31; sq += (key - o[i].w) >> 31;
            }
            sp += sq;
            sp += __shfl_xor_sync(0xffffffffu, sp, 1);
            sp += __shfl_xor_sync(0xffffffffu, sp, 2);
            const int grp = 9 - (int)(sp >> 3);
            const bool down = grp < 5;
            const uint32_t tp = grp * 8 + (sp & 7);
            sts32_lt(sm + MI_PERM + tp * 4, tid >> 2, tid & 3, 1);
            sts32_lt(sm + MI_SKEY + sp * 4, key, tid & 3, 1);
            sts64_lt(sm + MI_NREC + tid * 2, boundary(down ? grp : 9 - grp) * 16 + (sp & 7) * 2 + (down ? -14 : 0),
                     down ? ~0u : sp < 4 ? 1u : 0u, tid & 3, 1);
        }
        bar_arrive(10, 640);
        bar_sync(9, 544);
        if (tid == 0) STAMP(25);
        {
            uint2 nr[4];
#pragma unroll
            for (int j = 0; j < 4; j++) nr[j] = lds64(sm + MI_NREC + ((rec[j] >> 11) & 1016u));
            const uint32_t cap = split_cap(sm) << 7;
#pragma unroll
            for (int j = 0; j < 4; j++) {
                if (nr[j].y == 1u) {
                    nr[j].y = 0u;
                    if (rk[j] >= cap) { rk[j] -= cap; nr[j].x -= 6; nr[j].y = ~0u; }
                }
                const uint32_t off = ((rk[j] >> 4) & ~15u) | ((rk[j] >> 7) & 1u);
                const uint32_t ps = min(nr[j].x + (off ^ nr[j].y), (uint32_t)TRASH);
                sts32(sb + SM_LIST + ps * 4, rec[j] & 16383u);
                sts32(sb + SM_EL + ps * 4, sb + SM_EA + (gb + lane + 32 * j) * 32);
            }
        }
        if (tid == 0) STAMP(11);
        bar_arrive(11, 640);
        bar_sync(9, 544);
    }
    if (tid == 0) STAMP(13);

    Consts k;
    k.w3[0] = lds128(sb + SM_W3G + f * 1024 + lane * 16);
    k.w3[1] = lds128(sb + SM_W3G + f * 1024 + 512 + lane * 16);
    k.par = tag;
    k.q8 = q * 8;
    k.pb = reinterpret_cast<const unsigned char*>(gP) + f * 64 + q * 16;
    int dm;
    bool slow;
    {
        const int l = min(lane, 9);
        const int cap = split_cap(sm);
        dm = lds32(sm + MI_SKEY + (9 - l) * 32) >> 7;
        if (l == 0) dm = max(dm, (int)(lds32(sm + MI_SKEY) >> 7) - cap);
        if (l == 9) dm = cap;
        const int nt = (dm + 1) >> 1;
        const int other = __shfl_sync(0xffffffffu, nt, (10 - l) % 10);
        const int lim = l == 0 ? 16 : l == 5 ? 24 : (l == 1 || l == 9) ? 37 : 21;
        slow = __any_sync(0xffffffffu, nt + other > lim) || lds32(sm + MI_SLOW) != 0;
    }
    auto load_wu = [&]() {
        if (tid == 544) {
            tma_store_wait();
#pragma unroll
            for (int b = 0; b < 4; b++) tma_load(sb + SM_W + b * 16384, &tm_wu, (b & 1) * 64, (b >> 1) * 128, sm + MI_MB + 8);
        }
        __syncwarp();
    };
    if (slow) {
        load_wu();
        k.id = lds128(sm + MI_ID + lane * 16);
        mbar_wait0(sm + MI_MB + 16);
        slow_path(sb, e_attr, src, dst, E, k);
    } else {
        const int tsw = (int)__reduce_max_sync(0xffffffffu, (uint32_t)boundary(wg));
        const int dA = (int)__reduce_max_sync(0xffffffffu, lane == wg ? dm : 0);
        const int dB = (int)__reduce_max_sync(0xffffffffu, lane == 9 - wg ? dm : 0);
        const int t = tsw - ((dA + 1) >> 1);
        const uint32_t la = sb + SM_LIST + g * 8;
        k.id = lds128(sm + MI_ID + lane * 16);
        float qi[2][4], acc[2][4];
        {
            const uint2 r = lds64(sm + MI_PERM + wg * 32 + q * 8 + ((wg == 0 && q >= 2) ? 272 : 0));
            load_q(qi, sb, r.x, r.y, f, g);
        }
#pragma unroll
        for (int i = 0; i < 8; i++) (&acc[0][0])[i] = 0.f;
        Tile x0, y0;
        fetch(x0, la + t * 64, k);
        uint2 en = lds64(la + t * 64 + 64), eo = lds64(la + (SM_EL - SM_LIST) + t * 64);
        auto group_switch = [&]() {
            flush_agg(tile_addr(sb + SM_AGG, lds32(sm + MI_PERM + wg * 32 + g * 4), 4 * f + q), acc);
            const uint2 r = lds64(sm + MI_PERM + (9 - wg) * 32 + q * 8);
            load_q(qi, sb, r.x, r.y, f, g);
#pragma unroll
            for (int i = 0; i < 8; i++) {
                const float v = __shfl_xor_sync(0xffffffffu, (&acc[0][0])[i], 2);
                (&acc[0][0])[i] = (wg == 0 && q < 2) ? v : 0.f;
            }
        };
        mbar_wait0(sm + MI_MB + 24);
        if (tid == 0) STAMP(27);
        uint32_t lp = la + t * 64;
        auto step = [&](Tile& st, Tile& nx) {
            const uint2 ea0 = lds64(eo.x | k.q8), ea1 = lds64(eo.y | k.q8);
            if (__builtin_expect(stale(st, st, k), 0)) {
#pragma unroll 1
                for (int it = 0; it < SPIN_LIMIT; it++) {
                    fetch(st, lp, k);
                    if (!stale(st, st, k)) break;
                }
            }
            nx.p0 = ldg128_rlx(k.pb + (size_t)en.x * 256);
            nx.p1 = ldg128_rlx(k.pb + (size_t)en.y * 256);
            en = lds64(lp + 128);
            eo = lds64(lp + (SM_EL - SM_LIST) + 64);
            float c[2][2][4];
#pragma unroll
            for (int u = 0; u < 2; u++) {
                mma16_c(c[u][0], k.id.x, k.id.y, k.id.z, k.id.w, u ? st.p0.z : st.p0.x, u ? st.p0.w : st.p0.y, qi[u]);
                mma16_c(c[u][1], k.id.x, k.id.y, k.id.z, k.id.w, u ? st.p1.z : st.p1.x, u ? st.p1.w : st.p1.y, qi[u]);
            }
#pragma unroll
            for (int u = 0; u < 2; u++) {
                mma16(c[u][0], k.w3[u].x, k.w3[u].y, k.w3[u].z, k.w3[u].w, ea0.x, ea0.y);
                mma16(c[u][1], k.w3[u].x, k.w3[u].y, k.w3[u].z, k.w3[u].w, ea1.x, ea1.y);
            }
#pragma unroll
            for (int u = 0; u < 2; u++)
#pragma unroll
                for (int n = 0; n < 2; n++)
#pragma unroll
                    for (int i = 0; i < 4; i++) acc[u][i] += silu_half(c[u][n][i]);
            lp += 64;
        };
        auto revalidate = [&]() {
            if (__builtin_expect(stale(x0, x0, k), 0)) {
#pragma unroll 1
                for (int it = 0; it < SPIN_LIMIT; it++) {
                    fetch(x0, lp, k);
                    if (!stale(x0, x0, k)) break;
                }
            }
        };
        auto half = [&](const uint4& p, uint2 ea) {
            float c[2][4];
#pragma unroll
            for (int u = 0; u < 2; u++) mma16_c(c[u], k.id.x, k.id.y, k.id.z, k.id.w, u ? p.z : p.x, u ? p.w : p.y, qi[u]);
#pragma unroll
            for (int u = 0; u < 2; u++) mma16(c[u], k.w3[u].x, k.w3[u].y, k.w3[u].z, k.w3[u].w, ea.x, ea.y);
#pragma unroll
            for (int u = 0; u < 2; u++)
#pragma unroll
                for (int i = 0; i < 4; i++) acc[u][i] += silu_half(c[u][i]);
        };
        if (dA & 1) {
            const uint2 ea = lds64(eo.y | k.q8);
            revalidate();
            const uint4 p = x0.p1;
            x0.p0 = ldg128_rlx(k.pb + (size_t)en.x * 256);
            x0.p1 = ldg128_rlx(k.pb + (size_t)en.y * 256);
            en = lds64(lp + 128);
            eo = lds64(lp + (SM_EL - SM_LIST) + 64);
            half(p, ea);
            lp += 64;
        }
        int rem = dA >> 1;
#pragma unroll 1
        for (int ph = 0; ph < 2; ph++) {
#pragma unroll 1
            for (; rem >= 2; rem -= 2) {
                step(x0, y0);
                step(y0, x0);
            }
            if (rem) {
                step(x0, y0);
                x0 = y0;
            }
            if (ph == 0) {
                group_switch();
                load_wu();
                mbar_wait0(sm + MI_MB + 16);
                __syncwarp();
                rem = dB >> 1;
            }
        }
        if (dB & 1) {
            const uint2 ea = lds64(eo.x | k.q8);
            revalidate();
            half(x0.p0, ea);
        }
        flush_agg(tile_addr(sb + SM_AGG, lds32(sm + MI_PERM + (9 - wg) * 32 + g * 4), 4 * f + q), acc);
    }
    if (lane == 0 && f == 0) STAMP(14 + wg);

    fence_async();
    __syncwarp();
    if (lane == 0) asm volatile("mbarrier.arrive.shared::cta.b64 _, [%0];" ::"r"(sm + MI_MB + 32) : "memory");
    bar_sync(5 + wg, 128);
    if ((tid & 127) == 0) sts32(sm + MI_SEG + wg * 4, atoms_add(sm + MI_TICKET, 1));
    bar_sync(5 + wg, 128);
    const int role = (int)__reduce_max_sync(0xffffffffu, lds32(sm + MI_SEG + wg * 4));
    if (role == 4) return;
    {
        const int half = role >> 1, h = role & 1;
        float acc[20];
        const uint64_t da = make_desc(sb + SM_W + h * 16384);
        mbar_wait0(sm + MI_MB + 8);
        wg_fence();
        {
            const uint64_t db = make_desc(sb + SM_XS + half * 5120);
#pragma unroll
            for (int ks = 0; ks < 8; ks++) wgmma_n40(acc, da + ks * 128, db + (ks >> 2) * 640 + (ks & 3) * 2, ks);
        }
        wg_commit();
        mbar_wait0(sm + MI_MB + 32);
        __syncwarp();
        if (role == 3 && (tid & 127) == 0) STAMP(19);
        wg_fence();
        {
            const uint64_t db = make_desc(sb + SM_AGG + half * 5120);
#pragma unroll
            for (int ks = 0; ks < 8; ks++) wgmma_n40(acc, da + 2048 + ks * 128, db + (ks >> 2) * 640 + (ks & 3) * 2, 1);
        }
        wg_commit();
        const int t2 = tid & 127, r8 = t2 >> 3, c8 = t2 & 7;
        wg_wait<0>();
        if (role == 3 && (tid & 127) == 0) STAMP(20);
        const uint32_t ot = sb + SM_EA + role * 6144;
        {
            const int mi = lane >> 3, r = lane & 7;
            const uint32_t a = ot + ((mi >> 1) * 8 + r) * 128 + (((f * 2 + (mi & 1)) ^ r) << 4);
            uint32_t v[10];
#pragma unroll
            for (int i = 0; i < 10; i++) v[i] = pack_bf16(silu_half(0.5f * acc[2 * i]), silu_half(0.5f * acc[2 * i + 1]));
            stsm_x4_trans(a, v[0], v[1], v[2], v[3]);
            stsm_x4_trans(a + 2048, v[4], v[5], v[6], v[7]);
            stsm_x2_trans(a + 4096, v[8], v[9]);
        }
        bar_sync(5 + wg, 128);
        {
            const int lim = min(min(N - cta * NPC, NPC) - half * 40, 40);
            __nv_bfloat16* op = out + (size_t)(cta * NPC + half * 40 + r8) * D + h * 64 + c8 * 8;
            uint4 v[3];
#pragma unroll
            for (int p = 0; p < 3; p++) v[p] = lds128(ot + r8 * 128 + ((c8 ^ (r8 & 7)) << 4) + p * 2048);
#pragma unroll
            for (int p = 0; p < 3; p++)
                if (r8 + 16 * p < lim) stg128(op + 16 * p * D, v[p]);
        }
        if (role == 3 && (tid & 127) == 0) STAMP(21);
    }
}

__global__ void fb_zero(int n) {
    for (int i = blockIdx.x * blockDim.x + threadIdx.x; i < n; i += gridDim.x * blockDim.x) g_aggf[i] = 0.f;
}
__global__ void fb_edge(const __nv_bfloat16* x, const __nv_bfloat16* e_attr, const int* src, const int* dst,
                        const __nv_bfloat16* w_msg, int E) {
    __shared__ float in[2 * D + DE];
    for (int e = blockIdx.x; e < E; e += gridDim.x) {
        int s = src[e], d = dst[e], c = threadIdx.x;
        __syncthreads();
        in[c] = __bfloat162float(x[(size_t)s * D + c]);
        in[D + c] = __bfloat162float(x[(size_t)d * D + c]);
        if (c < DE) in[2 * D + c] = __bfloat162float(e_attr[(size_t)e * DE + c]);
        __syncthreads();
        float a = 0.f;
        for (int k = 0; k < 2 * D + DE; k++) a = fmaf(in[k], __bfloat162float(w_msg[k * D + c]), a);
        atomicAdd(&g_aggf[(size_t)d * D + c], a / (1.f + __expf(-a)));
    }
}
__global__ void fb_node(const __nv_bfloat16* x, const __nv_bfloat16* w_upd, __nv_bfloat16* out, int N) {
    __shared__ float in[2 * D];
    for (int n = blockIdx.x; n < N; n += gridDim.x) {
        int c = threadIdx.x;
        __syncthreads();
        in[c] = __bfloat162float(x[(size_t)n * D + c]);
        in[D + c] = g_aggf[(size_t)n * D + c];
        __syncthreads();
        float a = 0.f;
        for (int k = 0; k < 2 * D; k++) a = fmaf(in[k], __bfloat162float(w_upd[k * D + c]), a);
        out[(size_t)n * D + c] = __float2bfloat16(a / (1.f + __expf(-a)));
    }
}

}

extern "C" void kernel_launch(void* const* d_in, const int* in_sizes, int n_in, void* d_out, int out_size) {
    const __nv_bfloat16* x = (const __nv_bfloat16*)d_in[0];
    const __nv_bfloat16* e_attr = (const __nv_bfloat16*)d_in[1];
    const int* src = (const int*)d_in[2];
    const int* dst = (const int*)d_in[3];
    const __nv_bfloat16* w_msg = (const __nv_bfloat16*)d_in[4];
    const __nv_bfloat16* w_upd = (const __nv_bfloat16*)d_in[5];
    __nv_bfloat16* out = (__nv_bfloat16*)d_out;
    const int N = in_sizes[0] / D, E = in_sizes[2];

    typedef CUresult (*EncodeFn)(CUtensorMap*, CUtensorMapDataType, cuuint32_t, void*, const cuuint64_t*, const cuuint64_t*,
                                 const cuuint32_t*, const cuuint32_t*, CUtensorMapInterleave, CUtensorMapSwizzle,
                                 CUtensorMapL2promotion, CUtensorMapFloatOOBfill);
    static int mode = -1;
    static void *pP = nullptr, *pSeg = nullptr, *pEp = nullptr;
    static EncodeFn encode = nullptr;
    if (mode < 0) {
        int dev = 0, sms = 0, nb = 0;
        cudaGetDevice(&dev);
        cudaDeviceGetAttribute(&sms, cudaDevAttrMultiProcessorCount, dev);
        cudaError_t e = cudaFuncSetAttribute(mpnn_kernel, cudaFuncAttributeMaxDynamicSharedMemorySize, SM_ALLOC);
        if (e == cudaSuccess) e = cudaOccupancyMaxActiveBlocksPerMultiprocessor(&nb, mpnn_kernel, NT, SM_ALLOC);
        if (e == cudaSuccess) e = cudaGetSymbolAddress(&pP, g_P);
        if (e == cudaSuccess) e = cudaGetSymbolAddress(&pSeg, g_seg);
        if (e == cudaSuccess) e = cudaGetSymbolAddress(&pEp, g_epoch);
        void* fn = nullptr;
        cudaDriverEntryPointQueryResult qr;
        if (e == cudaSuccess) e = cudaGetDriverEntryPoint("cuTensorMapEncodeTiled", &fn, cudaEnableDefault, &qr);
        encode = (EncodeFn)fn;
        mode = (e == cudaSuccess && nb >= 1 && sms >= G && encode != nullptr) ? 1 : 0;
        (void)cudaGetLastError();
    }
    bool fast = mode == 1 && N >= 1 && N <= NMAX && E <= EMAX && (E & 1) == 0;
    CUtensorMap tm[5];
    if (fast) {
        void* base[5] = {(void*)x, (void*)w_msg, (void*)w_upd, pP, (void*)out};
        const cuuint64_t rows[5] = {(cuuint64_t)N, 2 * D + DE, 2 * D, NMAX, (cuuint64_t)N};
        const cuuint32_t boxr[5] = {ROWS, 128, 128, NPC, NPC};
        for (int i = 0; i < 4 && fast; i++) {
            const cuuint64_t dims[2] = {D, rows[i]}, strides[1] = {D * 2};
            const cuuint32_t box[2] = {64, boxr[i]}, es[2] = {1, 1};
            fast = encode(&tm[i], CU_TENSOR_MAP_DATA_TYPE_BFLOAT16, 2, base[i], dims, strides, box, es, CU_TENSOR_MAP_INTERLEAVE_NONE,
                          CU_TENSOR_MAP_SWIZZLE_128B, CU_TENSOR_MAP_L2_PROMOTION_NONE, CU_TENSOR_MAP_FLOAT_OOB_FILL_NONE) == CUDA_SUCCESS;
        }
    }
    if (fast) {
        mpnn_kernel<<<G, NT, SM_ALLOC, cudaStreamPerThread>>>(e_attr, src, dst, w_msg, w_upd, out, (__nv_bfloat16*)pP, (uint32_t*)pSeg,
                                                              (unsigned long long*)pEp, N, E, tm[0], tm[1], tm[2], tm[3]);
    } else if ((long long)N * D <= 4 * 1024 * 1024) {
        fb_zero<<<256, 256, 0, cudaStreamPerThread>>>(N * D);
        fb_edge<<<2048, D, 0, cudaStreamPerThread>>>(x, e_attr, src, dst, w_msg, E);
        fb_node<<<2048, D, 0, cudaStreamPerThread>>>(x, w_upd, out, N);
    }
}
```

```cpp
#include <cuda.h>
#include <cuda_runtime.h>
#include <cuda_bf16.h>
#include <stdint.h>

namespace {

constexpr int D = 128;
constexpr int DE = 16;
constexpr int G = 132;
constexpr int NPC = 76;
constexpr int ROWS = 80;
constexpr int EPC = 1216;
constexpr int NT = 640;
constexpr int NMAX = G * NPC;
constexpr int EMAX = G * EPC;
constexpr int SEGCAP = 32;

constexpr int NTILE = 120;
constexpr int SM_XS = 0;
constexpr int SM_W = 20480;
constexpr int SM_AGG = SM_W + 65536;
constexpr int EAROWS = 1536;
constexpr int SM_EA = SM_AGG + 20480;
constexpr int SM_LIST = SM_EA + EAROWS * 32;
constexpr int TRASH = (NTILE + 4) * 16;
constexpr int SM_EL = SM_LIST + 8000;
constexpr int SM_EG = SM_EL + 8000;
constexpr int SM_W3F = SM_EG + 13312;
constexpr int SM_W3G = SM_W3F + 4096;
constexpr int SM_MISC = SM_W3G + 4096;
constexpr int SM_STG = SM_AGG;
constexpr int SM_TOTAL = SM_MISC + 3328;
constexpr int SM_ALLOC = SM_TOTAL + 1024;
constexpr int MI_SEG = 0;
constexpr int MI_SLOW = 544;
constexpr int MI_ECNT = 548;
constexpr int MI_TICKET = 552;
constexpr int MI_KEY = 560;
constexpr int MI_MB = 3264;
constexpr int MI_TAG = 1072;
constexpr int MI_PERM = 1088;
constexpr int MI_SKEY = 1408;
constexpr int MI_NREC = 1728;
constexpr int MI_ID = 2752;

constexpr uint32_t W_EMPTY = 0xFFFFFFFFu;
constexpr uint32_t T_EMPTY = 0x7FFFFFFFu;
constexpr uint32_t T_OVF = 0x7FFFBFFFu;
constexpr int GBLIND = 4;
constexpr int HSLACK = 66;
constexpr int SPIN_LIMIT = 1 << 20;

__device__ __align__(256) __nv_bfloat16 g_P[(NMAX + G) * D];
__device__ __align__(256) uint32_t g_seg[G * G * SEGCAP];
__device__ __align__(256) unsigned long long g_epoch[32];
__device__ float g_aggf[4 * 1024 * 1024];
#define STAMP(i) do { } while (0)

__device__ __forceinline__ uint32_t smem_u32(const void* p) { return (uint32_t)__cvta_generic_to_shared(p); }
__device__ __forceinline__ void fence_async() { asm volatile("fence.proxy.async.shared::cta;" ::: "memory"); }
__device__ __forceinline__ void bar_sync(int id, int n) { asm volatile("bar.sync %0, %1;" ::"r"(id), "r"(n) : "memory"); }
__device__ __forceinline__ void bar_arrive(int id, int n) { asm volatile("bar.arrive %0, %1;" ::"r"(id), "r"(n) : "memory"); }
__device__ __forceinline__ uint32_t lds32(uint32_t a) { uint32_t v; asm volatile("ld.shared.u32 %0, [%1];" : "=r"(v) : "r"(a) : "memory"); return v; }
__device__ __forceinline__ uint2 lds64(uint32_t a) { uint2 v; asm volatile("ld.shared.v2.u32 {%0,%1}, [%2];" : "=r"(v.x), "=r"(v.y) : "r"(a) : "memory"); return v; }
__device__ __forceinline__ uint4 lds128(uint32_t a) { uint4 v; asm volatile("ld.shared.v4.u32 {%0,%1,%2,%3}, [%4];" : "=r"(v.x), "=r"(v.y), "=r"(v.z), "=r"(v.w) : "r"(a) : "memory"); return v; }
__device__ __forceinline__ void sts32(uint32_t a, uint32_t v) { asm volatile("st.shared.u32 [%0], %1;" ::"r"(a), "r"(v) : "memory"); }
__device__ __forceinline__ void sts128(uint32_t a, uint4 v) { asm volatile("st.shared.v4.u32 [%0], {%1,%2,%3,%4};" ::"r"(a), "r"(v.x), "r"(v.y), "r"(v.z), "r"(v.w) : "memory"); }
__device__ __forceinline__ void sts32_lt(uint32_t a, uint32_t v, uint32_t x, uint32_t lim) {
    asm volatile("{\n.reg .pred p;\nsetp.lt.u32 p, %2, %3;\n@p st.shared.u32 [%0], %1;\n}" ::"r"(a), "r"(v), "r"(x), "r"(lim) : "memory");
}
__device__ __forceinline__ void sts64_lt(uint32_t a, uint32_t v, uint32_t w, uint32_t x, uint32_t lim) {
    asm volatile("{\n.reg .pred p;\nsetp.lt.u32 p, %3, %4;\n@p st.shared.v2.u32 [%0], {%1, %2};\n}" ::"r"(a), "r"(v), "r"(w), "r"(x), "r"(lim) : "memory");
}
__device__ __forceinline__ void cp_async16_lt(uint32_t dst, const void* src, int x, int lim) {
    asm volatile("{\n.reg .pred p;\nsetp.lt.s32 p, %2, %3;\n@p cp.async.cg.shared.global [%0], [%1], 16;\n}" ::"r"(dst), "l"(src), "r"(x), "r"(lim) : "memory");
}
__device__ __forceinline__ uint32_t atoms_add_lt(uint32_t a, int d, uint32_t x, uint32_t lim) {
    uint32_t v = 0;
    asm volatile("{\n.reg .pred p;\nsetp.lt.u32 p, %3, %4;\n@p atom.shared.add.u32 %0, [%1], %2;\n}" : "+r"(v) : "r"(a), "r"(d), "r"(x), "r"(lim) : "memory");
    return v;
}
__device__ __forceinline__ uint32_t atoms_add(uint32_t a, int d) { uint32_t v; asm volatile("atom.shared.add.u32 %0, [%1], %2;" : "=r"(v) : "r"(a), "r"(d) : "memory"); return v; }
__device__ __forceinline__ uint4 ldg128(const void* p) { uint4 v; asm volatile("ld.global.v4.u32 {%0,%1,%2,%3}, [%4];" : "=r"(v.x), "=r"(v.y), "=r"(v.z), "=r"(v.w) : "l"(p) : "memory"); return v; }
__device__ __forceinline__ uint2 ldg64(const void* p) { uint2 v; asm volatile("ld.global.v2.u32 {%0,%1}, [%2];" : "=r"(v.x), "=r"(v.y) : "l"(p) : "memory"); return v; }
__device__ __forceinline__ void sts64(uint32_t a, uint32_t x, uint32_t y) { asm volatile("st.shared.v2.u32 [%0], {%1,%2};" ::"r"(a), "r"(x), "r"(y) : "memory"); }
__device__ __forceinline__ void stg128(void* p, uint4 v) { asm volatile("st.global.v4.u32 [%0], {%1,%2,%3,%4};" ::"l"(p), "r"(v.x), "r"(v.y), "r"(v.z), "r"(v.w) : "memory"); }
__device__ __forceinline__ uint32_t pack_bf16(float lo, float hi) {
    uint32_t r; asm("cvt.rn.bf16x2.f32 %0, %1, %2;" : "=r"(r) : "f"(hi), "f"(lo)); return r;
}
__device__ __forceinline__ float tanh_fast(float x) { float r; asm("tanh.approx.f32 %0, %1;" : "=f"(r) : "f"(x)); return r; }
__device__ __forceinline__ float silu_half(float h) { return fmaf(h, tanh_fast(h), h); }
__device__ __forceinline__ uint32_t movm(uint32_t a) { uint32_t d; asm volatile("movmatrix.sync.aligned.m8n8.trans.b16 %0, %1;" : "=r"(d) : "r"(a)); return d; }
__device__ __forceinline__ uint32_t shl_clamp(uint32_t v, uint32_t s) { uint32_t d; asm("shl.b32 %0, %1, %2;" : "=r"(d) : "r"(v), "r"(s)); return d; }
__device__ __forceinline__ void mma16(float (&d)[4], uint32_t a0, uint32_t a1, uint32_t a2, uint32_t a3, uint32_t b0, uint32_t b1) {
    asm("mma.sync.aligned.m16n8k16.row.col.f32.bf16.bf16.f32 {%0,%1,%2,%3}, {%4,%5,%6,%7}, {%8,%9}, {%0,%1,%2,%3};"
        : "+f"(d[0]), "+f"(d[1]), "+f"(d[2]), "+f"(d[3]) : "r"(a0), "r"(a1), "r"(a2), "r"(a3), "r"(b0), "r"(b1));
}
__device__ __forceinline__ void mma16_c(float (&d)[4], uint32_t a0, uint32_t a1, uint32_t a2, uint32_t a3, uint32_t b0, uint32_t b1, const float (&c)[4]) {
    asm("mma.sync.aligned.m16n8k16.row.col.f32.bf16.bf16.f32 {%0,%1,%2,%3}, {%4,%5,%6,%7}, {%8,%9}, {%10,%11,%12,%13};"
        : "=f"(d[0]), "=f"(d[1]), "=f"(d[2]), "=f"(d[3]) : "r"(a0), "r"(a1), "r"(a2), "r"(a3), "r"(b0), "r"(b1),
          "f"(c[0]), "f"(c[1]), "f"(c[2]), "f"(c[3]));
}
__device__ __forceinline__ void stsm_x4_trans(uint32_t addr, uint32_t r0, uint32_t r1, uint32_t r2, uint32_t r3) {
    asm volatile("stmatrix.sync.aligned.m8n8.x4.trans.shared.b16 [%0], {%1,%2,%3,%4};" ::"r"(addr), "r"(r0), "r"(r1), "r"(r2), "r"(r3) : "memory");
}

__device__ __forceinline__ uint64_t make_desc(uint32_t addr) {
    return (uint64_t)((addr & 0x3FFFF) >> 4) | ((uint64_t)64 << 16) | ((uint64_t)64 << 32) | ((uint64_t)1 << 62);
}
__device__ __forceinline__ void wg_fence() { asm volatile("wgmma.fence.sync.aligned;" ::: "memory"); }
__device__ __forceinline__ void wg_commit() { asm volatile("wgmma.commit_group.sync.aligned;" ::: "memory"); }
template <int N> __device__ __forceinline__ void wg_wait() { asm volatile("wgmma.wait_group.sync.aligned %0;" ::"n"(N) : "memory"); }
__device__ __forceinline__ void wgmma_n80(float (&d)[40], uint64_t da, uint64_t db, int scale_d) {
    asm volatile(
        "{\n.reg .pred p;\nsetp.ne.b32 p, %42, 0;\n"
        "wgmma.mma_async.sync.aligned.m64n80k16.f32.bf16.bf16 "
        "{%0,%1,%2,%3,%4,%5,%6,%7,%8,%9,%10,%11,%12,%13,%14,%15,%16,%17,%18,%19,"
        "%20,%21,%22,%23,%24,%25,%26,%27,%28,%29,%30,%31,%32,%33,%34,%35,%36,%37,%38,%39}, "
        "%40, %41, p, 1, 1, 1, 0;\n}\n"
        : "+f"(d[0]), "+f"(d[1]), "+f"(d[2]), "+f"(d[3]), "+f"(d[4]), "+f"(d[5]), "+f"(d[6]), "+f"(d[7]), "+f"(d[8]), "+f"(d[9]),
          "+f"(d[10]), "+f"(d[11]), "+f"(d[12]), "+f"(d[13]), "+f"(d[14]), "+f"(d[15]), "+f"(d[16]), "+f"(d[17]), "+f"(d[18]), "+f"(d[19]),
          "+f"(d[20]), "+f"(d[21]), "+f"(d[22]), "+f"(d[23]), "+f"(d[24]), "+f"(d[25]), "+f"(d[26]), "+f"(d[27]), "+f"(d[28]), "+f"(d[29]),
          "+f"(d[30]), "+f"(d[31]), "+f"(d[32]), "+f"(d[33]), "+f"(d[34]), "+f"(d[35]), "+f"(d[36]), "+f"(d[37]), "+f"(d[38]), "+f"(d[39])
        : "l"(da), "l"(db), "r"(scale_d));
}

__device__ __forceinline__ void wgmma_n40(float (&d)[20], uint64_t da, uint64_t db, int scale_d) {
    asm volatile(
        "{\n.reg .pred p;\nsetp.ne.b32 p, %22, 0;\n"
        "wgmma.mma_async.sync.aligned.m64n40k16.f32.bf16.bf16 "
        "{%0,%1,%2,%3,%4,%5,%6,%7,%8,%9,%10,%11,%12,%13,%14,%15,%16,%17,%18,%19}, "
        "%20, %21, p, 1, 1, 1, 0;\n}\n"
        : "+f"(d[0]), "+f"(d[1]), "+f"(d[2]), "+f"(d[3]), "+f"(d[4]), "+f"(d[5]), "+f"(d[6]), "+f"(d[7]), "+f"(d[8]), "+f"(d[9]),
          "+f"(d[10]), "+f"(d[11]), "+f"(d[12]), "+f"(d[13]), "+f"(d[14]), "+f"(d[15]), "+f"(d[16]), "+f"(d[17]), "+f"(d[18]), "+f"(d[19])
        : "l"(da), "l"(db), "r"(scale_d));
}
__device__ __forceinline__ void stsm_x2_trans(uint32_t addr, uint32_t r0, uint32_t r1) {
    asm volatile("stmatrix.sync.aligned.m8n8.x2.trans.shared.b16 [%0], {%1,%2};" ::"r"(addr), "r"(r0), "r"(r1) : "memory");
}
__device__ __forceinline__ uint4 ldg128_rlx(const void* p) { uint4 v; asm volatile("ld.relaxed.gpu.global.v4.u32 {%0,%1,%2,%3}, [%4];" : "=r"(v.x), "=r"(v.y), "=r"(v.z), "=r"(v.w) : "l"(p) : "memory"); return v; }
__device__ __forceinline__ void stg128_rlx(void* p, uint4 v) { asm volatile("st.relaxed.gpu.global.v4.u32 [%0], {%1,%2,%3,%4};" ::"l"(p), "r"(v.x), "r"(v.y), "r"(v.z), "r"(v.w) : "memory"); }

__device__ __forceinline__ unsigned long long ldg64_rlx(const void* p) { unsigned long long v; asm volatile("ld.relaxed.gpu.global.u64 %0, [%1];" : "=l"(v) : "l"(p) : "memory"); return v; }
__device__ __forceinline__ void hint_arrive(unsigned long long* p) { asm volatile("red.relaxed.gpu.global.add.u64 [%0], 1;" ::"l"(p) : "memory"); }
__device__ __forceinline__ void hint_wait(const unsigned long long* p, unsigned long long target) {
#pragma unroll 1
    for (int it = 0; it < SPIN_LIMIT; it++)
        if (ldg64_rlx(p) >= target) break;
}

__host__ __device__ constexpr int boundary(int k) { return k == 0 ? 8 : 24 + 21 * k; }
__device__ __forceinline__ uint32_t tile_addr(uint32_t base, int row, int c) {
    return base + (c >> 3) * 10240 + row * 128 + (((c & 7) ^ (row & 7)) << 4);
}

__device__ __forceinline__ uint32_t split_cap(uint32_t sm) {
    const int d0 = lds32(sm + MI_SKEY) >> 7, d4 = lds32(sm + MI_SKEY + 16) >> 7, d72 = lds32(sm + MI_SKEY + 288) >> 7;
    return max(d4, d0 - ((d72 + 1) & ~1));
}

struct Tile { uint4 p0, p1; };
struct Consts { uint4 w3[2]; uint4 id; uint32_t par, q8; const unsigned char* pb; };

__device__ __forceinline__ void fetch(Tile& st, uint32_t la, const Consts& k) {
    uint2 e = lds64(la);
    st.p0 = ldg128_rlx(k.pb + (size_t)e.x * 256);
    st.p1 = ldg128_rlx(k.pb + (size_t)e.y * 256);
}
__device__ __forceinline__ bool stale(const Tile& a, const Tile& b, const Consts& k) {
    uint32_t t, u;
    asm("lop3.b32 %0, %1, %2, %3, 0x7E;" : "=r"(t) : "r"(a.p0.x), "r"(a.p1.x), "r"(k.par));
    asm("lop3.b32 %0, %1, %2, %3, 0x7E;" : "=r"(u) : "r"(b.p0.x), "r"(b.p1.x), "r"(k.par));
    asm("lop3.b32 %0, %1, %2, 1, 0xA8;" : "=r"(t) : "r"(t), "r"(u));
    return __any_sync(0xffffffffu, t != 0);
}
__device__ __forceinline__ void validate(Tile& a, Tile& b, uint32_t la, const Consts& k) {
    if (__builtin_expect(stale(a, b, k), 0)) {
#pragma unroll 1
        for (int it = 0; it < SPIN_LIMIT; it++) {
            fetch(a, la, k);
            fetch(b, la + 64, k);
            if (!stale(a, b, k)) break;
        }
    }
}
__device__ __forceinline__ void tile_mma(float (&acc)[2][4], const Tile& st, uint2 eo, const float (&qi)[2][4], const Consts& k) {
    const uint2 ea0 = lds64(eo.x | k.q8), ea1 = lds64(eo.y | k.q8);
    float c[2][2][4];
#pragma unroll
    for (int u = 0; u < 2; u++) {
        mma16_c(c[u][0], k.id.x, k.id.y, k.id.z, k.id.w, u ? st.p0.z : st.p0.x, u ? st.p0.w : st.p0.y, qi[u]);
        mma16_c(c[u][1], k.id.x, k.id.y, k.id.z, k.id.w, u ? st.p1.z : st.p1.x, u ? st.p1.w : st.p1.y, qi[u]);
    }
#pragma unroll
    for (int u = 0; u < 2; u++) {
        mma16(c[u][0], k.w3[u].x, k.w3[u].y, k.w3[u].z, k.w3[u].w, ea0.x, ea0.y);
        mma16(c[u][1], k.w3[u].x, k.w3[u].y, k.w3[u].z, k.w3[u].w, ea1.x, ea1.y);
    }
#pragma unroll
    for (int u = 0; u < 2; u++)
#pragma unroll
        for (int n = 0; n < 2; n++)
#pragma unroll
            for (int i = 0; i < 4; i++) acc[u][i] += silu_half(c[u][n][i]);
}
__device__ __forceinline__ void load_q(float (&qi)[2][4], uint32_t sb, int ra, int rb, int f, int g) {
    const uint4 a = lds128(tile_addr(sb + SM_AGG, ra, 4 * f + (g >> 1))), b = lds128(tile_addr(sb + SM_AGG, rb, 4 * f + (g >> 1)));
    const uint32_t sel = (g & 1) ? 0x3244u : 0x1044u;
    qi[0][0] = 0.5f * __uint_as_float(__byte_perm(a.x, 0, sel)); qi[0][1] = 0.5f * __uint_as_float(__byte_perm(b.x, 0, sel));
    qi[0][2] = 0.5f * __uint_as_float(__byte_perm(a.y, 0, sel)); qi[0][3] = 0.5f * __uint_as_float(__byte_perm(b.y, 0, sel));
    qi[1][0] = 0.5f * __uint_as_float(__byte_perm(a.z, 0, sel)); qi[1][1] = 0.5f * __uint_as_float(__byte_perm(b.z, 0, sel));
    qi[1][2] = 0.5f * __uint_as_float(__byte_perm(a.w, 0, sel)); qi[1][3] = 0.5f * __uint_as_float(__byte_perm(b.w, 0, sel));
}
__device__ __forceinline__ void flush_agg(uint32_t addr, const float (&acc)[2][4]) {
    uint4 v;
    v.x = movm(pack_bf16(acc[0][0], acc[0][1]));
    v.y = movm(pack_bf16(acc[0][2], acc[0][3]));
    v.z = movm(pack_bf16(acc[1][0], acc[1][1]));
    v.w = movm(pack_bf16(acc[1][2], acc[1][3]));
    sts128(addr, v);
}

__device__ __forceinline__ void tma_load(uint32_t dst, const CUtensorMap* tm, int c0, int c1, uint32_t mbar) {
    asm volatile("cp.async.bulk.tensor.2d.shared::cluster.global.mbarrier::complete_tx::bytes [%0], [%1, {%2, %3}], [%4];"
                 ::"r"(dst), "l"(tm), "r"(c0), "r"(c1), "r"(mbar) : "memory");
}
__device__ __forceinline__ void tma_store(const CUtensorMap* tm, int c0, int c1, uint32_t src) {
    asm volatile("cp.async.bulk.tensor.2d.global.shared::cta.bulk_group [%0, {%1, %2}], [%3];" ::"l"(tm), "r"(c0), "r"(c1), "r"(src) : "memory");
    asm volatile("cp.async.bulk.commit_group;" ::: "memory");
}
__device__ __forceinline__ void tma_store_wait() { asm volatile("cp.async.bulk.wait_group.read 0;" ::: "memory"); }
__device__ __forceinline__ void mbar_wait0(uint32_t a) {
    for (int it = 0; it < SPIN_LIMIT; it++) {
        uint32_t ok;
        asm volatile("{\n.reg .pred p;\nmbarrier.try_wait.parity.shared::cta.b64 p, [%1], 0;\nselp.u32 %0, 1, 0, p;\n}" : "=r"(ok) : "r"(a) : "memory");
        if (ok) break;
    }
}

__device__ __noinline__ void slow_path(uint32_t sb, const __nv_bfloat16* e_attr, const int* src, const int* dst, int E, Consts k) {
    const int tid = threadIdx.x, lane = tid & 31, wg = tid >> 7, f = (tid >> 5) & 3, g = lane >> 2, q = lane & 3, cta = blockIdx.x;
    const uint32_t s_deg = sb + SM_MISC + MI_KEY;
    float acc[2][2][4];
    for (int i = 0; i < 16; i++) (&acc[0][0][0])[i] = 0.f;
    int scan = 0, state = 0, row = 0;
    bool more = true;
    while (more) {
        more = false;
        __syncthreads();
        if (tid < ROWS) sts32(s_deg + tid * 4, 0);
        for (int i = tid; i < EAROWS * 2; i += NT) sts128(sb + SM_EA + i * 16, make_uint4(0, 0, 0, 0));
        for (int i = tid; i < (NTILE + 4) * 16; i += NT) sts32(sb + SM_LIST + i * 4, NMAX + cta);
        __syncthreads();
        while (true) {
            const int e = scan + tid;
            if (state == 0) {
                state = 2;
                if (e < E) {
                    int dn = dst[e];
                    if (dn / NPC == cta) { state = 1; row = dn - cta * NPC; }
                }
            }
            if (state == 1) {
                uint32_t rank = atoms_add(s_deg + row * 4, 1);
                if (rank < 18) {
                    uint32_t pos = ((row >> 3) * 9 + (rank >> 1)) * 16 + (row & 7) * 2 + (rank & 1);
                    sts32(sb + SM_LIST + pos * 4, (uint32_t)src[e]);
                    sts128(sb + SM_EA + pos * 32, ldg128(e_attr + (size_t)e * DE));
                    sts128(sb + SM_EA + pos * 32 + 16, ldg128(e_attr + (size_t)e * DE + 8));
                    state = 2;
                }
            }
            if (__syncthreads_or(state == 1)) { more = true; break; }
            scan += NT;
            state = 0;
            if (scan >= E) break;
        }
#pragma unroll
        for (int b = 0; b < 2; b++) {
            const int grp = 2 * wg + b;
            const int mx = min((int)__reduce_max_sync(0xffffffffu, lds32(s_deg + (grp * 8 + g) * 4)), 18);
            float qi[2][4];
            load_q(qi, sb, grp * 8 + 2 * q, grp * 8 + 2 * q + 1, f, g);
            for (int t = 0; t * 2 < mx; t++) {
                const int tile = grp * 9 + t;
                Tile st, s2;
                const uint32_t la = sb + SM_LIST + tile * 64 + g * 8;
                fetch(st, la, k);
                fetch(s2, la + 64, k);
                validate(st, s2, la, k);
                tile_mma(acc[b], st, make_uint2(sb + SM_EA + tile * 512 + g * 64, sb + SM_EA + tile * 512 + g * 64 + 32), qi, k);
            }
        }
    }
    __syncwarp();
    flush_agg(tile_addr(sb + SM_AGG, wg * 16 + g, 4 * f + q), acc[0]);
    flush_agg(tile_addr(sb + SM_AGG, wg * 16 + 8 + g, 4 * f + q), acc[1]);
}

__global__ void __launch_bounds__(NT, 1)
mpnn_kernel(const __nv_bfloat16* __restrict__ e_attr, const int* __restrict__ src, const int* __restrict__ dst,
            const __nv_bfloat16* __restrict__ w_msg, const __nv_bfloat16* __restrict__ w_upd,
            __nv_bfloat16* __restrict__ out, __nv_bfloat16* __restrict__ gP, uint32_t* __restrict__ gseg,
            unsigned long long* __restrict__ gepoch, int N, int E,
            const __grid_constant__ CUtensorMap tm_x, const __grid_constant__ CUtensorMap tm_wm,
            const __grid_constant__ CUtensorMap tm_wu, const __grid_constant__ CUtensorMap tm_p) {
    extern __shared__ unsigned char smem_raw[];
    const uint32_t sb = (smem_u32(smem_raw) + 1023u) & ~1023u;
    const int tid = threadIdx.x, warp = tid >> 5, lane = tid & 31;
    const int wg = warp >> 2, f = warp & 3, g = lane >> 2, q = lane & 3;
    const int cta = blockIdx.x;
    const int wgu = (int)__reduce_max_sync(0xffffffffu, (uint32_t)wg);
    const uint32_t sm = sb + SM_MISC;
    if (tid == 0) STAMP(0);

    uint2 d2 = make_uint2(~0u, 0), s2;
    {
        const int e0 = ((tid >> 4) * G + cta) * 32 + (tid & 15) * 2;
        if (tid < EPC / 2 && e0 < E) {
            d2 = ldg64(dst + e0);
            s2 = ldg64(src + e0);
        }
    }
    unsigned long long cnt0 = 0;
    if (tid == 576) cnt0 = ldg64_rlx(gepoch);
    sts128(sb + SM_STG + tid * 16, make_uint4(W_EMPTY, W_EMPTY, W_EMPTY, W_EMPTY));
    if (tid < 416) sts128(sb + SM_STG + 10240 + tid * 16, make_uint4(W_EMPTY, W_EMPTY, W_EMPTY, W_EMPTY));
    else if (tid < 636) sts32(sm + (tid - 416) * 4, tid >= 556 ? 127 - (tid - 556) : tid == 553);
    if (warp == 19) {
        if (lane == 31) {
            asm volatile("mbarrier.init.shared::cta.b64 [%0], 1;" ::"r"(sm + MI_MB) : "memory");
            asm volatile("mbarrier.init.shared::cta.b64 [%0], 1;" ::"r"(sm + MI_MB + 8) : "memory");
            asm volatile("mbarrier.init.shared::cta.b64 [%0], 96;" ::"r"(sm + MI_MB + 16) : "memory");
            asm volatile("mbarrier.init.shared::cta.b64 [%0], 96;" ::"r"(sm + MI_MB + 24) : "memory");
            asm volatile("mbarrier.init.shared::cta.b64 [%0], 20;" ::"r"(sm + MI_MB + 32) : "memory");
            sts64(sm + MI_NREC + 127 * 8, 0x40000000u, 0u);
        }
        __syncwarp();
        bar_arrive(3, 640);
        if (lane == 31) {
            fence_async();
            asm volatile("mbarrier.arrive.expect_tx.shared::cta.b64 _, [%0], %1;" ::"r"(sm + MI_MB), "r"(20480 + 65536 + 4096) : "memory");
            asm volatile("mbarrier.arrive.expect_tx.shared::cta.b64 _, [%0], %1;" ::"r"(sm + MI_MB + 8), "r"(65536) : "memory");
#pragma unroll
            for (int b = 0; b < 4; b++) tma_load(sb + SM_W + b * 16384, &tm_wm, (b & 1) * 64, (b >> 1) * 128, sm + MI_MB);
            asm volatile("cp.async.bulk.shared::cluster.global.mbarrier::complete_tx::bytes [%0], [%1], 4096, [%2];"
                         ::"r"(sb + SM_W3F), "l"(w_msg + 2 * D * D), "r"(sm + MI_MB) : "memory");
            tma_load(sb + SM_XS, &tm_x, 0, cta * NPC, sm + MI_MB);
            tma_load(sb + SM_XS + 10240, &tm_x, 64, cta * NPC, sm + MI_MB);
            asm volatile("prefetch.tensormap [%0];" ::"l"(&tm_p) : "memory");
            asm volatile("prefetch.tensormap [%0];" ::"l"(&tm_wu) : "memory");
        }
        __syncwarp();
    } else {
        bar_sync(3, 640);
    }
    if (tid == 0) STAMP(23);
    if (tid >= 636)
        asm volatile("prefetch.global.L2 [%0];" ::"l"(reinterpret_cast<const unsigned char*>(w_upd) + min(cta * 4 + (tid - 636), 511) * 128));
    if (d2.x != ~0u) {
        const uint32_t dc0 = d2.x / NPC, dc1 = d2.y / NPC;
        const uint32_t r0 = atoms_add(sm + MI_SEG + dc0 * 4, 1), r1 = atoms_add(sm + MI_SEG + dc1 * 4, 1);
        const uint32_t w0 = s2.x | (((tid << 8) + d2.x - dc0 * NPC) << 14), w1 = s2.y | (((tid << 8) + 128 + d2.y - dc1 * NPC) << 14);
        sts32_lt(sb + SM_STG + dc0 * 128 + (r0 & 7) * 16 + (r0 >> 3) * 4, w0, r0, SEGCAP);
        sts32_lt(sb + SM_STG + dc1 * 128 + (r1 & 7) * 16 + (r1 >> 3) * 4, w1, r1, SEGCAP);
    }
    if (tid == 576) {
        cnt0 = cnt0 / G + 1;
        sts64(sm + MI_TAG, (uint32_t)cnt0, (uint32_t)(cnt0 >> 32));
    }
    if (tid == 0) STAMP(24);
    __syncthreads();
    const uint32_t tag = lds32(sm + MI_TAG);
    const uint32_t parw = tag << 31;
    {
        uint4 v[2];
        uint32_t cn[2];
#pragma unroll
        for (int i = 0; i < 2; i++) {
            v[i] = lds128(sb + SM_STG + tid * 16 + i * 10240);
            cn[i] = lds32(sm + MI_SEG + min((tid >> 3) + i * 80, 135) * 4);
        }
#pragma unroll
        for (int i = 0; i < 2; i++) {
            uint32_t tl = T_EMPTY;
            if (cn[i] > 24) {
                const uint32_t w = v[i].w;
                if (w != W_EMPTY) tl = (((w >> 21) * ROWS + ((w >> 14) & 127u)) << 14) | (w & 16383u);
                if (cn[i] > SEGCAP) tl = T_OVF;
            }
            v[i].w = tl | parw;
            if (i == 0 || tid < 416) stg128_rlx(gseg + (size_t)cta * (G * SEGCAP) + tid * 4 + i * 2560, v[i]);
        }
    }
    const uint32_t* bp = gseg + ((size_t)(tid >> 3) * G + cta) * SEGCAP + (tid & 7) * 4;
    uint4 v1 = make_uint4(W_EMPTY, W_EMPTY, W_EMPTY, T_EMPTY | parw), v0 = v1;
    auto prefill2 = [&]() {
        const uint32_t pr = NMAX + cta;
        if (tid < 496) sts128(sb + SM_LIST + tid * 16, make_uint4(pr, pr, pr, pr));
        if (tid >= 144) sts128(sb + SM_EL + (tid - 144) * 16, make_uint4(sb + SM_EA, sb + SM_EA, sb + SM_EA, sb + SM_EA));
        else if (tid >= 142) sts128(sb + SM_EA + (tid - 142) * 16, make_uint4(0, 0, 0, 0));
        else if (tid < 32) {
            uint32_t idf = shl_clamp(0x3F00u, (uint32_t)((g - 2 * q) << 4));
            sts128(sm + MI_ID + lane * 16, make_uint4(idf, 0, 0, idf));
        }
    };
    const uint32_t so = (((lane >> 4) & 1) * 8 + (lane & 7)) * 128 + (((f * 2 + ((lane >> 3) & 1)) ^ (lane & 7)) << 4);
    if (wgu < 2) {
        bar_arrive(2, 640);
        prefill2();
        mbar_wait0(sm + MI_MB);
        if (tid == 0) STAMP(1);
        if (tid == 255) {
            int eb = cta * EPC, ne = min(EPC, E - eb);
            if (ne > 0) asm volatile("cp.async.bulk.prefetch.L2.global [%0], %1;" ::"l"(e_attr + (size_t)eb * DE), "r"(ne * 32) : "memory");
        }
        float gacc[40];
        const uint64_t da = make_desc(sb + SM_W + wgu * 16384), db = make_desc(sb + SM_XS);
        wg_fence();
#pragma unroll
        for (int ks = 0; ks < 8; ks++) wgmma_n80(gacc, da + ks * 128, db + (ks >> 2) * 640 + (ks & 3) * 2, ks);
        wg_commit();
        const uint32_t keep = g == 0 ? 0xFFFEFFFEu : 0xFFFFFFFFu, setb = g == 0 ? (tag & 1u) * 0x10001u : 0u;
        wg_wait<0>();
        if (tid == 0) STAMP(2);
        bar_sync(7 + wg, 128);
#pragma unroll
        for (int j = 0; j < 5; j++)
            stsm_x4_trans(sb + SM_W + wg * 16384 + so + j * 2048,
                          (pack_bf16(gacc[8 * j], gacc[8 * j + 1]) & keep) | setb, (pack_bf16(gacc[8 * j + 2], gacc[8 * j + 3]) & keep) | setb,
                          (pack_bf16(gacc[8 * j + 4], gacc[8 * j + 5]) & keep) | setb, (pack_bf16(gacc[8 * j + 6], gacc[8 * j + 7]) & keep) | setb);
        fence_async();
        bar_arrive(5, 288);
        bar_sync(12, 288);
        if (tid == 0) STAMP(22);
        v0 = ldg128_rlx(bp);
        v1 = ldg128_rlx(bp + (size_t)68 * G * SEGCAP);
    } else if (wgu < 4) {
        bar_arrive(2, 640);
        prefill2();
        bar_sync(4, 384);
        v0 = ldg128_rlx(bp);
        v1 = ldg128_rlx(bp + (size_t)68 * G * SEGCAP);
        float gacc[40];
        const uint64_t da = make_desc(sb + SM_W + wgu * 16384), db = make_desc(sb + SM_XS);
        mbar_wait0(sm + MI_MB);
        __syncwarp();
        wg_fence();
#pragma unroll
        for (int ks = 0; ks < 8; ks++) wgmma_n80(gacc, da + ks * 128, db + (ks >> 2) * 640 + (ks & 3) * 2, ks);
        wg_commit();
        wg_wait<0>();
#pragma unroll
        for (int j = 0; j < 5; j++)
            stsm_x4_trans(sb + SM_AGG + (wg - 2) * 10240 + so + j * 2048,
                          pack_bf16(gacc[8 * j], gacc[8 * j + 1]), pack_bf16(gacc[8 * j + 2], gacc[8 * j + 3]),
                          pack_bf16(gacc[8 * j + 4], gacc[8 * j + 5]), pack_bf16(gacc[8 * j + 6], gacc[8 * j + 7]));
    } else {
        if (warp < 19) bar_arrive(2, 640);
        prefill2();
        if (tid >= 624)
            stg128_rlx(gP + (size_t)(NMAX + cta) * D + (tid - 624) * 8, make_uint4(0xFF00FF00u | (tag & 1u), 0xFF00FF00u, 0xFF00FF00u, 0xFF00FF00u));
        if (warp == 19) {
            bar_sync(2, 640);
            if (lane == 0) { STAMP(4); hint_arrive(gepoch); hint_wait(gepoch, (((unsigned long long)lds32(sm + MI_TAG + 4) << 32) | tag) * G - HSLACK); STAMP(7); }
            __syncwarp();
            bar_arrive(12, 288);
        } else {
            mbar_wait0(sm + MI_MB);
#pragma unroll 1
            for (int ff = f; ff < 4; ff += 3) {
                const uint32_t wa = sb + SM_W3F + (4 * q * D + 32 * ff + (g >> 1) * 8 + (g & 1)) * 2;
                uint32_t w[8];
#pragma unroll
                for (int i = 0; i < 8; i++) {
                    const int u = i >> 2, r = i & 3, o = 4 * u + 2 * (r & 1) + 2 * (r >> 1) * D;
                    unsigned short lo, hi;
                    asm volatile("ld.shared.u16 %0, [%1];" : "=h"(lo) : "r"(wa + o * 2));
                    asm volatile("ld.shared.u16 %0, [%1];" : "=h"(hi) : "r"(wa + (o + D) * 2));
                    asm("mul.bf16x2 %0, %1, %2;" : "=r"(w[i]) : "r"((uint32_t)lo | ((uint32_t)hi << 16)), "r"(0x3F003F00u));
                }
                sts128(sb + SM_W3G + ff * 1024 + lane * 16, make_uint4(w[0], w[1], w[2], w[3]));
                sts128(sb + SM_W3G + ff * 1024 + 512 + lane * 16, make_uint4(w[4], w[5], w[6], w[7]));
            }
        }
        bar_sync(4, 384);
        if (warp == 16) v0 = ldg128_rlx(bp);
    }
    if (warp >= 17) {
        if (warp == 17) {
            bar_sync(5, 288);
            if (lane == 0) {
                tma_store(&tm_p, 0, cta * NPC, sb + SM_W);
                tma_store(&tm_p, 64, cta * NPC, sb + SM_W + 16384);
                STAMP(3);
            }
            __syncwarp();
        }
        bar_sync(6, 640);
        const int n = min((int)lds32(sm + MI_ECNT), EAROWS);
        const unsigned char* geb = reinterpret_cast<const unsigned char*>(e_attr) + (lane & 1) * 16;
        const int n0 = lds32(sm + MI_SLOW) == 0 ? n : 0;
        const int r0 = 1 + (lane >> 1) + (warp - 17) * 32;
#pragma unroll
        for (int it = 0; it < GBLIND; it++)
#pragma unroll
            for (int j = 0; j < 2; j++) {
                const int r = r0 + it * 96 + j * 16;
                cp_async16_lt(sb + SM_EA + r * 32 + (lane & 1) * 16, geb + lds32(sb + SM_EG + r * 8), r, n0);
            }
        constexpr int GR = 28 - 2 * GBLIND;
        uint2 rc[GR];
#pragma unroll
        for (int j = 0; j < GR; j++) rc[j] = lds64(sb + SM_EG + (r0 + (GBLIND + (j >> 1)) * 96 + (j & 1) * 16) * 8);
#pragma unroll 1
        for (int r = r0 + (GBLIND + GR / 2) * 96; r < n0 + 16; r += 96) {
            cp_async16_lt(sb + SM_EA + r * 32 + (lane & 1) * 16, geb + lds32(sb + SM_EG + r * 8), r, n0);
            cp_async16_lt(sb + SM_EA + r * 32 + 512 + (lane & 1) * 16, geb + lds32(sb + SM_EG + r * 8 + 128), r + 16, n0);
        }
        bar_sync(10, 640);
#pragma unroll
        for (int j = 0; j < GR; j++) rc[j].y = lds32(sm + MI_NREC + 4 + ((rc[j].y >> 11) & 1016u));
#pragma unroll
        for (int ph = 0; ph < 2; ph++) {
#pragma unroll
            for (int j = 0; j < GR; j++) {
                const int r = r0 + (GBLIND + (j >> 1)) * 96 + (j & 1) * 16;
                cp_async16_lt(sb + SM_EA + r * 32 + (lane & 1) * 16, geb + rc[j].x, ((rc[j].y != 0u) == (ph == 0)) ? r : n0, n0);
            }
            asm volatile("cp.async.mbarrier.arrive.noinc.shared::cta.b64 [%0];" ::"r"(sm + MI_MB + 24 - ph * 8) : "memory");
            if (ph == 0 && tid == 544) STAMP(10);
        }
        if (tid == 544) STAMP(12);
        bar_sync(11, 640);
    } else {
        __syncwarp();
#pragma unroll 1
        for (int it = 0; it < SPIN_LIMIT; it++) {
            if (!__any_sync(0xffffffffu, (int)((v0.w ^ parw) | (v1.w ^ parw)) < 0)) break;
            if (it) __nanosleep(200);
            v0 = ldg128_rlx(bp);
            if (wg < 4) v1 = ldg128_rlx(bp + (size_t)68 * G * SEGCAP);
        }
        if (tid == 0) STAMP(8);
        const uint32_t lt = (1u << lane) - 1u;
        uint32_t en[8] = {v0.x, v1.x, v0.y, v1.y, v0.z, v1.z, W_EMPTY, W_EMPTY}, es[8], gb = 0;
        int gt = 0;
        auto count = [&](int i) {
            const uint32_t m = __ballot_sync(0xffffffffu, en[i] != W_EMPTY);
            es[i] = gt + __popc(m & lt);
            gt += __popc(m);
        };
        auto put = [&](int i) {
            const uint32_t el = en[i] >> 21;
            sts64_lt(sb + SM_EG + (gb + es[i]) * 8, (el + (el >> 5) * (G * 32 - 32) + ((tid >> 3) + (i & 1) * 68) * 32) * 32, en[i], en[i], W_EMPTY);
        };
#pragma unroll
        for (int i = 0; i < 6; i++) count(i);
        const bool deep = __any_sync(0xffffffffu, (v0.w & v1.w & T_EMPTY) != T_EMPTY);
        if (deep) {
#pragma unroll
            for (int r = 0; r < 2; r++) {
                const uint32_t tl = (r ? v1.w : v0.w) & T_EMPTY, er = tl >> 14, el = ((er >> 4) * 52429u) >> 18;
                if (tl == T_OVF) sts32(sm + MI_SLOW, 1);
                if (tl < T_OVF) en[6 + r] = (el << 21) | ((er - el * ROWS) << 14) | (tl & 16383u);
                count(6 + r);
            }
        }
        if (lane == 0) gb = atoms_add(sm + MI_ECNT, gt);
        gb = __shfl_sync(0xffffffffu, gb, 0);
        if (gb + gt > EAROWS || gt > 128) { sts32(sm + MI_SLOW, 1); gb = 0; gt = 0; }
#pragma unroll
        for (int i = 0; i < 6; i++) put(i);
        if (deep) { put(6); put(7); }
        __syncwarp();
        bar_arrive(6, 640);
        uint32_t rec[4], rk[4];
#pragma unroll
        for (int j = 0; j < 4; j++) rec[j] = lds32(sb + SM_EG + (gb + lane) * 8 + 4 + j * 256);
#pragma unroll
        for (int j = 0; j < 4; j++) {
            if (lane + 32 * j >= gt) rec[j] = W_EMPTY;
            rk[j] = 0;
            if (32 * j < gt) rk[j] = atoms_add_lt(sm + MI_KEY + ((rec[j] >> 12) & 508u), 128, rec[j], W_EMPTY);
        }
        bar_sync(9, 544);
        if (tid == 0) STAMP(9);
        if (warp < 10) {
            const uint32_t key = lds32(sm + MI_KEY + (tid >> 2) * 4);
            uint4 o[5];
#pragma unroll
            for (int i = 0; i < 5; i++) o[i] = lds128(sm + MI_KEY + (tid & 3) * 80 + i * 16);
            uint32_t sp = 0, sq = 0;
#pragma unroll
            for (int i = 0; i < 5; i++) {
                sp += (key - o[i].x) >> 31; sq += (key - o[i].y) >> 31;
                sp += (key - o[i].z) >> 31; sq += (key - o[i].w) >> 31;
            }
            sp += sq;
            sp += __shfl_xor_sync(0xffffffffu, sp, 1);
            sp += __shfl_xor_sync(0xffffffffu, sp, 2);
            const int grp = 9 - (int)(sp >> 3);
            const bool down = grp < 5;
            const uint32_t tp = grp * 8 + (sp & 7);
            sts32_lt(sm + MI_PERM + tp * 4, tid >> 2, tid & 3, 1);
            sts32_lt(sm + MI_SKEY + sp * 4, key, tid & 3, 1);
            sts64_lt(sm + MI_NREC + tid * 2, boundary(down ? grp : 9 - grp) * 16 + (sp & 7) * 2 + (down ? -14 : 0),
                     down ? ~0u : sp < 4 ? 1u : 0u, tid & 3, 1);
        }
        bar_arrive(10, 640);
        bar_sync(9, 544);
        if (tid == 0) STAMP(25);
        {
            uint2 nr[4];
#pragma unroll
            for (int j = 0; j < 4; j++) nr[j] = lds64(sm + MI_NREC + ((rec[j] >> 11) & 1016u));
            const uint32_t cap = split_cap(sm) << 7;
#pragma unroll
            for (int j = 0; j < 4; j++) {
                if (nr[j].y == 1u) {
                    nr[j].y = 0u;
                    if (rk[j] >= cap) { rk[j] -= cap; nr[j].x -= 6; nr[j].y = ~0u; }
                }
                const uint32_t off = ((rk[j] >> 4) & ~15u) | ((rk[j] >> 7) & 1u);
                const uint32_t ps = min(nr[j].x + (off ^ nr[j].y), (uint32_t)TRASH);
                sts32(sb + SM_LIST + ps * 4, rec[j] & 16383u);
                sts32(sb + SM_EL + ps * 4, sb + SM_EA + (gb + lane + 32 * j) * 32);
            }
        }
        if (tid == 0) STAMP(11);
        bar_arrive(11, 640);
        bar_sync(9, 544);
    }
    if (tid == 0) STAMP(13);

    Consts k;
    k.w3[0] = lds128(sb + SM_W3G + f * 1024 + lane * 16);
    k.w3[1] = lds128(sb + SM_W3G + f * 1024 + 512 + lane * 16);
    k.par = tag;
    k.q8 = q * 8;
    k.pb = reinterpret_cast<const unsigned char*>(gP) + f * 64 + q * 16;
    int dm;
    bool slow;
    {
        const int l = min(lane, 9);
        const int cap = split_cap(sm);
        dm = lds32(sm + MI_SKEY + (9 - l) * 32) >> 7;
        if (l == 0) dm = max(dm, (int)(lds32(sm + MI_SKEY) >> 7) - cap);
        if (l == 9) dm = cap;
        const int nt = (dm + 1) >> 1;
        const int other = __shfl_sync(0xffffffffu, nt, (10 - l) % 10);
        const int lim = l == 0 ? 16 : l == 5 ? 24 : (l == 1 || l == 9) ? 37 : 21;
        slow = __any_sync(0xffffffffu, nt + other > lim) || lds32(sm + MI_SLOW) != 0;
    }
    auto load_wu = [&]() {
        if (tid == 544) {
            tma_store_wait();
#pragma unroll
            for (int b = 0; b < 4; b++) tma_load(sb + SM_W + b * 16384, &tm_wu, (b & 1) * 64, (b >> 1) * 128, sm + MI_MB + 8);
        }
        __syncwarp();
    };
    if (slow) {
        load_wu();
        k.id = lds128(sm + MI_ID + lane * 16);
        mbar_wait0(sm + MI_MB + 16);
        slow_path(sb, e_attr, src, dst, E, k);
    } else {
        const int tsw = (int)__reduce_max_sync(0xffffffffu, (uint32_t)boundary(wg));
        const int dA = (int)__reduce_max_sync(0xffffffffu, lane == wg ? dm : 0);
        const int dB = (int)__reduce_max_sync(0xffffffffu, lane == 9 - wg ? dm : 0);
        const int t = tsw - ((dA + 1) >> 1);
        const uint32_t la = sb + SM_LIST + g * 8;
        k.id = lds128(sm + MI_ID + lane * 16);
        float qi[2][4], acc[2][4];
        {
            const uint2 r = lds64(sm + MI_PERM + wg * 32 + q * 8 + ((wg == 0 && q >= 2) ? 272 : 0));
            load_q(qi, sb, r.x, r.y, f, g);
        }
#pragma unroll
        for (int i = 0; i < 8; i++) (&acc[0][0])[i] = 0.f;
        Tile x0, y0;
        fetch(x0, la + t * 64, k);
        uint2 en = lds64(la + t * 64 + 64), eo = lds64(la + (SM_EL - SM_LIST) + t * 64);
        auto group_switch = [&]() {
            flush_agg(tile_addr(sb + SM_AGG, lds32(sm + MI_PERM + wg * 32 + g * 4), 4 * f + q), acc);
            const uint2 r = lds64(sm + MI_PERM + (9 - wg) * 32 + q * 8);
            load_q(qi, sb, r.x, r.y, f, g);
#pragma unroll
            for (int i = 0; i < 8; i++) {
                const float v = __shfl_xor_sync(0xffffffffu, (&acc[0][0])[i], 2);
                (&acc[0][0])[i] = (wg == 0 && q < 2) ? v : 0.f;
            }
        };
        mbar_wait0(sm + MI_MB + 24);
        if (tid == 0) STAMP(27);
        uint32_t lp = la + t * 64;
        auto step = [&](Tile& st, Tile& nx) {
            const uint2 ea0 = lds64(eo.x | k.q8), ea1 = lds64(eo.y | k.q8);
            if (__builtin_expect(stale(st, st, k), 0)) {
#pragma unroll 1
                for (int it = 0; it < SPIN_LIMIT; it++) {
                    fetch(st, lp, k);
                    if (!stale(st, st, k)) break;
                }
            }
            nx.p0 = ldg128_rlx(k.pb + (size_t)en.x * 256);
            nx.p1 = ldg128_rlx(k.pb + (size_t)en.y * 256);
            en = lds64(lp + 128);
            eo = lds64(lp + (SM_EL - SM_LIST) + 64);
            float c[2][2][4];
#pragma unroll
            for (int u = 0; u < 2; u++) {
                mma16_c(c[u][0], k.id.x, k.id.y, k.id.z, k.id.w, u ? st.p0.z : st.p0.x, u ? st.p0.w : st.p0.y, qi[u]);
                mma16_c(c[u][1], k.id.x, k.id.y, k.id.z, k.id.w, u ? st.p1.z : st.p1.x, u ? st.p1.w : st.p1.y, qi[u]);
            }
#pragma unroll
            for (int u = 0; u < 2; u++) {
                mma16(c[u][0], k.w3[u].x, k.w3[u].y, k.w3[u].z, k.w3[u].w, ea0.x, ea0.y);
                mma16(c[u][1], k.w3[u].x, k.w3[u].y, k.w3[u].z, k.w3[u].w, ea1.x, ea1.y);
            }
#pragma unroll
            for (int u = 0; u < 2; u++)
#pragma unroll
                for (int n = 0; n < 2; n++)
#pragma unroll
                    for (int i = 0; i < 4; i++) acc[u][i] += silu_half(c[u][n][i]);
            lp += 64;
        };
        auto revalidate = [&]() {
            if (__builtin_expect(stale(x0, x0, k), 0)) {
#pragma unroll 1
                for (int it = 0; it < SPIN_LIMIT; it++) {
                    fetch(x0, lp, k);
                    if (!stale(x0, x0, k)) break;
                }
            }
        };
        auto half = [&](const uint4& p, uint2 ea) {
            float c[2][4];
#pragma unroll
            for (int u = 0; u < 2; u++) mma16_c(c[u], k.id.x, k.id.y, k.id.z, k.id.w, u ? p.z : p.x, u ? p.w : p.y, qi[u]);
#pragma unroll
            for (int u = 0; u < 2; u++) mma16(c[u], k.w3[u].x, k.w3[u].y, k.w3[u].z, k.w3[u].w, ea.x, ea.y);
#pragma unroll
            for (int u = 0; u < 2; u++)
#pragma unroll
                for (int i = 0; i < 4; i++) acc[u][i] += silu_half(c[u][i]);
        };
        if (dA & 1) {
            const uint2 ea = lds64(eo.y | k.q8);
            revalidate();
            const uint4 p = x0.p1;
            x0.p0 = ldg128_rlx(k.pb + (size_t)en.x * 256);
            x0.p1 = ldg128_rlx(k.pb + (size_t)en.y * 256);
            en = lds64(lp + 128);
            eo = lds64(lp + (SM_EL - SM_LIST) + 64);
            half(p, ea);
            lp += 64;
        }
        int rem = dA >> 1;
#pragma unroll 1
        for (int ph = 0; ph < 2; ph++) {
#pragma unroll 1
            for (; rem >= 2; rem -= 2) {
                step(x0, y0);
                step(y0, x0);
            }
            if (rem) {
                step(x0, y0);
                x0 = y0;
            }
            if (ph == 0) {
                group_switch();
                load_wu();
                mbar_wait0(sm + MI_MB + 16);
                __syncwarp();
                rem = dB >> 1;
            }
        }
        if (dB & 1) {
            const uint2 ea = lds64(eo.x | k.q8);
            revalidate();
            half(x0.p0, ea);
        }
        flush_agg(tile_addr(sb + SM_AGG, lds32(sm + MI_PERM + (9 - wg) * 32 + g * 4), 4 * f + q), acc);
    }
    if (lane == 0 && f == 0) STAMP(14 + wg);

    fence_async();
    __syncwarp();
    if (lane == 0) asm volatile("mbarrier.arrive.shared::cta.b64 _, [%0];" ::"r"(sm + MI_MB + 32) : "memory");
    const int wbar = wg < 2 ? 1 + wg : 11 + wg;
    bar_sync(wbar, 128);
    if ((tid & 127) == 0) sts32(sm + MI_SEG + wg * 4, atoms_add(sm + MI_TICKET, 1));
    bar_sync(wbar, 128);
    const int role = (int)__reduce_max_sync(0xffffffffu, lds32(sm + MI_SEG + wg * 4));
    if (role == 4) return;
    {
        const int half = role >> 1, h = role & 1;
        float acc[20];
        const uint64_t da = make_desc(sb + SM_W + h * 16384);
        mbar_wait0(sm + MI_MB + 8);
        wg_fence();
        {
            const uint64_t db = make_desc(sb + SM_XS + half * 5120);
#pragma unroll
            for (int ks = 0; ks < 8; ks++) wgmma_n40(acc, da + ks * 128, db + (ks >> 2) * 640 + (ks & 3) * 2, ks);
        }
        wg_commit();
        mbar_wait0(sm + MI_MB + 32);
        __syncwarp();
        if (role == 3 && (tid & 127) == 0) STAMP(19);
        wg_fence();
        {
            const uint64_t db = make_desc(sb + SM_AGG + half * 5120);
#pragma unroll
            for (int ks = 0; ks < 8; ks++) wgmma_n40(acc, da + 2048 + ks * 128, db + (ks >> 2) * 640 + (ks & 3) * 2, 1);
        }
        wg_commit();
        const int t2 = tid & 127, r8 = t2 >> 3, c8 = t2 & 7;
        wg_wait<0>();
        if (role == 3 && (tid & 127) == 0) STAMP(20);
        const uint32_t ot = sb + SM_EA + role * 6144;
        {
            const int mi = lane >> 3, r = lane & 7;
            const uint32_t a = ot + ((mi >> 1) * 8 + r) * 128 + (((f * 2 + (mi & 1)) ^ r) << 4);
            uint32_t v[10];
#pragma unroll
            for (int i = 0; i < 10; i++) v[i] = pack_bf16(silu_half(0.5f * acc[2 * i]), silu_half(0.5f * acc[2 * i + 1]));
            stsm_x4_trans(a, v[0], v[1], v[2], v[3]);
            stsm_x4_trans(a + 2048, v[4], v[5], v[6], v[7]);
            stsm_x2_trans(a + 4096, v[8], v[9]);
        }
        bar_sync(wbar, 128);
        {
            const int lim = min(min(N - cta * NPC, NPC) - half * 40, 40);
            __nv_bfloat16* op = out + (size_t)(cta * NPC + half * 40 + r8) * D + h * 64 + c8 * 8;
            uint4 v[3];
#pragma unroll
            for (int p = 0; p < 3; p++) v[p] = lds128(ot + r8 * 128 + ((c8 ^ (r8 & 7)) << 4) + p * 2048);
#pragma unroll
            for (int p = 0; p < 3; p++)
                if (r8 + 16 * p < lim) stg128(op + 16 * p * D, v[p]);
        }
        if (role == 3 && (tid & 127) == 0) STAMP(21);
    }
}

__global__ void fb_zero(int n) {
    for (int i = blockIdx.x * blockDim.x + threadIdx.x; i < n; i += gridDim.x * blockDim.x) g_aggf[i] = 0.f;
}
__global__ void fb_edge(const __nv_bfloat16* x, const __nv_bfloat16* e_attr, const int* src, const int* dst,
                        const __nv_bfloat16* w_msg, int E) {
    __shared__ float in[2 * D + DE];
    for (int e = blockIdx.x; e < E; e += gridDim.x) {
        int s = src[e], d = dst[e], c = threadIdx.x;
        __syncthreads();
        in[c] = __bfloat162float(x[(size_t)s * D + c]);
        in[D + c] = __bfloat162float(x[(size_t)d * D + c]);
        if (c < DE) in[2 * D + c] = __bfloat162float(e_attr[(size_t)e * DE + c]);
        __syncthreads();
        float a = 0.f;
        for (int k = 0; k < 2 * D + DE; k++) a = fmaf(in[k], __bfloat162float(w_msg[k * D + c]), a);
        atomicAdd(&g_aggf[(size_t)d * D + c], a / (1.f + __expf(-a)));
    }
}
__global__ void fb_node(const __nv_bfloat16* x, const __nv_bfloat16* w_upd, __nv_bfloat16* out, int N) {
    __shared__ float in[2 * D];
    for (int n = blockIdx.x; n < N; n += gridDim.x) {
        int c = threadIdx.x;
        __syncthreads();
        in[c] = __bfloat162float(x[(size_t)n * D + c]);
        in[D + c] = g_aggf[(size_t)n * D + c];
        __syncthreads();
        float a = 0.f;
        for (int k = 0; k < 2 * D; k++) a = fmaf(in[k], __bfloat162float(w_upd[k * D + c]), a);
        out[(size_t)n * D + c] = __float2bfloat16(a / (1.f + __expf(-a)));
    }
}

}

extern "C" void kernel_launch(void* const* d_in, const int* in_sizes, int n_in, void* d_out, int out_size) {
    const __nv_bfloat16* x = (const __nv_bfloat16*)d_in[0];
    const __nv_bfloat16* e_attr = (const __nv_bfloat16*)d_in[1];
    const int* src = (const int*)d_in[2];
    const int* dst = (const int*)d_in[3];
    const __nv_bfloat16* w_msg = (const __nv_bfloat16*)d_in[4];
    const __nv_bfloat16* w_upd = (const __nv_bfloat16*)d_in[5];
    __nv_bfloat16* out = (__nv_bfloat16*)d_out;
    const int N = in_sizes[0] / D, E = in_sizes[2];

    typedef CUresult (*EncodeFn)(CUtensorMap*, CUtensorMapDataType, cuuint32_t, void*, const cuuint64_t*, const cuuint64_t*,
                                 const cuuint32_t*, const cuuint32_t*, CUtensorMapInterleave, CUtensorMapSwizzle,
                                 CUtensorMapL2promotion, CUtensorMapFloatOOBfill);
    static int mode = -1;
    static void *pP = nullptr, *pSeg = nullptr, *pEp = nullptr;
    static EncodeFn encode = nullptr;
    if (mode < 0) {
        int dev = 0, sms = 0, nb = 0;
        cudaGetDevice(&dev);
        cudaDeviceGetAttribute(&sms, cudaDevAttrMultiProcessorCount, dev);
        cudaError_t e = cudaFuncSetAttribute(mpnn_kernel, cudaFuncAttributeMaxDynamicSharedMemorySize, SM_ALLOC);
        if (e == cudaSuccess) e = cudaOccupancyMaxActiveBlocksPerMultiprocessor(&nb, mpnn_kernel, NT, SM_ALLOC);
        if (e == cudaSuccess) e = cudaGetSymbolAddress(&pP, g_P);
        if (e == cudaSuccess) e = cudaGetSymbolAddress(&pSeg, g_seg);
        if (e == cudaSuccess) e = cudaGetSymbolAddress(&pEp, g_epoch);
        void* fn = nullptr;
        cudaDriverEntryPointQueryResult qr;
        if (e == cudaSuccess) e = cudaGetDriverEntryPoint("cuTensorMapEncodeTiled", &fn, cudaEnableDefault, &qr);
        encode = (EncodeFn)fn;
        mode = (e == cudaSuccess && nb >= 1 && sms >= G && encode != nullptr) ? 1 : 0;
        (void)cudaGetLastError();
    }
    bool fast = mode == 1 && N >= 1 && N <= NMAX && E <= EMAX && (E & 1) == 0;
    CUtensorMap tm[4];
    if (fast) {
        void* base[4] = {(void*)x, (void*)w_msg, (void*)w_upd, pP};
        const cuuint64_t rows[4] = {(cuuint64_t)N, 2 * D + DE, 2 * D, NMAX};
        const cuuint32_t boxr[4] = {ROWS, 128, 128, NPC};
        for (int i = 0; i < 4 && fast; i++) {
            const cuuint64_t dims[2] = {D, rows[i]}, strides[1] = {D * 2};
            const cuuint32_t box[2] = {64, boxr[i]}, es[2] = {1, 1};
            fast = encode(&tm[i], CU_TENSOR_MAP_DATA_TYPE_BFLOAT16, 2, base[i], dims, strides, box, es, CU_TENSOR_MAP_INTERLEAVE_NONE,
                          CU_TENSOR_MAP_SWIZZLE_128B, CU_TENSOR_MAP_L2_PROMOTION_NONE, CU_TENSOR_MAP_FLOAT_OOB_FILL_NONE) == CUDA_SUCCESS;
        }
    }
    if (fast) {
        mpnn_kernel<<<G, NT, SM_ALLOC, cudaStreamPerThread>>>(e_attr, src, dst, w_msg, w_upd, out, (__nv_bfloat16*)pP, (uint32_t*)pSeg,
                                                              (unsigned long long*)pEp, N, E, tm[0], tm[1], tm[2], tm[3]);
    } else if ((long long)N * D <= 4 * 1024 * 1024) {
        fb_zero<<<256, 256, 0, cudaStreamPerThread>>>(N * D);
        fb_edge<<<2048, D, 0, cudaStreamPerThread>>>(x, e_attr, src, dst, w_msg, E);
        fb_node<<<2048, D, 0, cudaStreamPerThread>>>(x, w_upd, out, N);
    }
}
```
